```python
import torch

def _softmax(x, axis=-1):
    return torch.softmax(x, dim=axis)

def _gelu(x):
    return torch.nn.functional.gelu(x, approximate='tanh')

def _silu(x):
    return torch.nn.functional.silu(x)

def _sigmoid(x):
    return torch.sigmoid(x)

def _layernorm(x, axis=-1, eps=1e-05):
    m = x.mean(dim=axis, keepdim=True)
    v = x.var(dim=axis, keepdim=True, unbiased=False)
    return (x - m) / torch.sqrt(v + eps)

def _scatter_add(tgt, idx, src, axis=0):
    return tgt.clone().index_add_(axis, idx, src)

def _segment_sum(src, seg, n):
    out = torch.zeros((n,) + src.shape[1:], dtype=src.dtype)
    return out.index_add_(0, seg, src)

def _pad(x, pw):
    flat = tuple((v for pair in reversed(pw) for v in pair))
    return torch.nn.functional.pad(x, flat)
kernel_name = 'concat_heads__softmax_full_mha__memory_aug_recurrent_mem_tr__prompt'

def setup_inputs():

    _w = lambda a: (lambda t: t.to(torch.bfloat16) if t.is_floating_point() else t)(torch.as_tensor(a))

    def _A_setup():
        B, S, D = (1, 2048, 640)
        return {'x': _w((lambda *s: torch.randn(*s, dtype=torch.bfloat16) * 0.2)(B, S, D)), 'wqkv': _w((lambda *s: torch.randn(*s, dtype=torch.bfloat16) * 0.2)(D, 3 * D)), 'wo': _w((lambda *s: torch.randn(*s, dtype=torch.bfloat16) * 0.05)(D, D))}
    _A_in = _A_setup()

    def _B_setup():
        B, S, Dm = (1, 2048, 640)
        H, Dh = (32, 128)
        M, seg = (8, 32)
        seg = min(seg, S)
        S = S // seg * seg
        return {'x': _w((lambda *s: torch.randn(*s, dtype=torch.bfloat16) * 0.05)(B, S, Dm)), 'mem0': _w((lambda *s: torch.randn(*s, dtype=torch.bfloat16) * 0.8)(B, M, Dm)), 'Wq': _w((lambda *s: torch.randn(*s, dtype=torch.bfloat16) * 1.6)(Dm, H, Dh) * Dm ** (-0.5)), 'Wk': _w((lambda *s: torch.randn(*s, dtype=torch.bfloat16) * 1.6)(Dm, H, Dh) * Dm ** (-0.5)), 'Wv': _w((lambda *s: torch.randn(*s, dtype=torch.bfloat16) * 0.8)(Dm, H, Dh) * Dm ** (-0.5)), 'Wo': _w((lambda *s: torch.randn(*s, dtype=torch.bfloat16) * 0.8)(H, Dh, Dm) * (H * Dh) ** (-0.5)), 'seg_len': seg}
    _B_in = _B_setup()
    return {'A_x': _A_in['x'], 'A_wqkv': _A_in['wqkv'], 'A_wo': _A_in['wo'], 'B_x': _B_in['x'], 'B_mem0': _B_in['mem0'], 'B_Wq': _B_in['Wq'], 'B_Wk': _B_in['Wk'], 'B_Wv': _B_in['Wv'], 'B_Wo': _B_in['Wo'], 'B_seg_len': _B_in['seg_len']}

def reference(A_x, A_wqkv, A_wo, B_x, B_mem0, B_Wq, B_Wk, B_Wv, B_Wo, B_seg_len):

    def _A_ref(x, wqkv, wo):
        B, S, D = x.shape
        H = 32
        Dh = D // H
        qkv = (lambda x, *d: x.permute(*d))((x @ wqkv).reshape(B, S, 3, H, Dh), 2, 0, 3, 1, 4)
        q, k, v = (qkv[0], qkv[1], qkv[2])
        scale = Dh ** (-0.5)
        scores = torch.einsum('bhqd,bhkd->bhqk', q, k) * scale
        p = _softmax(scores, axis=-1)
        o = torch.einsum('bhqk,bhkd->bhqd', p, v)
        return (lambda x, *d: x.permute(*d))(o, 0, 2, 1, 3).reshape(B, S, D) @ wo

    def _B_ref(x, mem0, Wq, Wk, Wv, Wo, seg_len):
        B, S, Dm = x.shape
        H, Dh = (Wq.shape[1], Wq.shape[2])
        M = mem0.shape[1]
        scale = Dh ** (-0.5)
        n_seg = S // seg_len
        L = M + seg_len
        idx = torch.arange(L)
        mask = (idx[:, None] < M) | (idx[:, None] >= idx[None, :])
        mem = mem0
        outs = []
        for s in range(n_seg):
            xs = x[:, s * seg_len:(s + 1) * seg_len, :].clone()
            h = torch.concatenate([mem, xs], axis=1)
            q = torch.einsum('btd,dhe->bhte', h, Wq)
            k = torch.einsum('btd,dhe->bhte', h, Wk)
            v = torch.einsum('btd,dhe->bhte', h, Wv)
            scores = torch.einsum('bhqe,bhke->bhqk', q, k) * scale
            scores = torch.where(mask[None, None], scores, -1000000000.0)
            p = _softmax(scores, axis=-1)
            o = torch.einsum('bhqk,bhke->bhqe', p, v)
            o = torch.einsum('bhte,hed->btd', o, Wo)
            mem = o[:, :M, :].clone()
            outs.append(o[:, M:, :])
        return torch.concatenate(outs, axis=1)
    a = _A_ref(A_x, A_wqkv, A_wo)
    b = _B_ref(B_x, B_mem0, B_Wq, B_Wk, B_Wv, B_Wo, B_seg_len)
    return torch.concatenate([a, b], axis=-1)
```

```cpp
#define HAVE_REC 1

#include <cuda_runtime.h>
#include <cuda_bf16.h>
#include <cuda.h>
#include <stdint.h>
#include <stdio.h>

constexpr int S_LEN = 2048;
constexpr int DM = 640;
constexpr int OUT_LD = 1280;
constexpr int A_H = 32, A_DH = 20;
constexpr int B_H = 32, B_DH = 128, B_M = 8, B_SEG = 32, B_NSEG = 64;
constexpr int B_HD = B_H * B_DH;

typedef __nv_bfloat16 bf16;

__device__ __forceinline__ uint32_t smem_u32(const void* p) { return (uint32_t)__cvta_generic_to_shared(p); }
__device__ __forceinline__ uint32_t pack_bf16(float lo, float hi) {
  uint32_t r; asm("cvt.rn.bf16x2.f32 %0, %1, %2;" : "=r"(r) : "f"(hi), "f"(lo)); return r;
}
__device__ __forceinline__ float bf16lo(uint32_t v) { return __uint_as_float(v << 16); }
__device__ __forceinline__ float bf16hi(uint32_t v) { return __uint_as_float(v & 0xFFFF0000u); }
__device__ __forceinline__ float ex2f(float x) { float r; asm("ex2.approx.ftz.f32 %0, %1;" : "=f"(r) : "f"(x)); return r; }

__device__ __forceinline__ void mbar_init(uint32_t bar, uint32_t cnt) { asm volatile("mbarrier.init.shared::cta.b64 [%0], %1;" :: "r"(bar), "r"(cnt) : "memory"); }
__device__ __forceinline__ void mbar_expect_tx(uint32_t bar, uint32_t bytes) { asm volatile("mbarrier.arrive.expect_tx.shared::cta.b64 _, [%0], %1;" :: "r"(bar), "r"(bytes) : "memory"); }
__device__ __forceinline__ void mbar_arrive(uint32_t bar) { asm volatile("mbarrier.arrive.shared::cta.b64 _, [%0];" :: "r"(bar) : "memory"); }
__device__ __forceinline__ void mbar_arrive_cluster(uint32_t bar_cluster_addr) { asm volatile("mbarrier.arrive.release.cluster.shared::cluster.b64 _, [%0];" :: "r"(bar_cluster_addr) : "memory"); }
__device__ __forceinline__ bool mbar_try(uint32_t bar, uint32_t parity) {
  uint32_t ok;
  asm volatile("{\n.reg .pred p;\nmbarrier.try_wait.parity.shared::cta.b64 p, [%1], %2;\nselp.u32 %0, 1, 0, p;\n}" : "=r"(ok) : "r"(bar), "r"(parity) : "memory");
  return ok;
}
__device__ __forceinline__ bool mbar_try_cluster(uint32_t bar, uint32_t parity) {
  uint32_t ok;
  asm volatile("{\n.reg .pred p;\nmbarrier.try_wait.parity.acquire.cluster.shared::cta.b64 p, [%1], %2;\nselp.u32 %0, 1, 0, p;\n}" : "=r"(ok) : "r"(bar), "r"(parity) : "memory");
  return ok;
}
constexpr uint32_t SPIN_LIMIT = 1u << 22;
__device__ unsigned g_timeout_flag;
__device__ __forceinline__ void mbar_wait(uint32_t bar, uint32_t parity) {
  uint32_t n = 0;
  while (!mbar_try(bar, parity)) { if (++n > SPIN_LIMIT) { g_timeout_flag = 1; break; } }
}
__device__ __forceinline__ void mbar_wait_cluster(uint32_t bar, uint32_t parity) {
  uint32_t n = 0;
  while (!mbar_try_cluster(bar, parity)) { if (++n > SPIN_LIMIT) { g_timeout_flag = 2; break; } }
}
__device__ __forceinline__ void fence_mbar_init() { asm volatile("fence.mbarrier_init.release.cluster;" ::: "memory"); }
__device__ __forceinline__ void fence_proxy_async() { asm volatile("fence.proxy.async.shared::cta;" ::: "memory"); }
__device__ __forceinline__ void bar_sync(int id, int n) { __syncwarp(); asm volatile("bar.sync %0, %1;" :: "r"(id), "r"(n) : "memory"); }
__device__ __forceinline__ void bar_arrive(int id, int n) { __syncwarp(); asm volatile("bar.arrive %0, %1;" :: "r"(id), "r"(n) : "memory"); }

__device__ __forceinline__ void tma_load_2d(uint32_t dst, const CUtensorMap* tm, int c0, int c1, uint32_t bar) {
  asm volatile("cp.async.bulk.tensor.2d.shared::cta.global.mbarrier::complete_tx::bytes [%0], [%1, {%3, %4}], [%2];"
               :: "r"(dst), "l"(tm), "r"(bar), "r"(c0), "r"(c1) : "memory");
}
__device__ __forceinline__ void tma_load_3d(uint32_t dst, const CUtensorMap* tm, int c0, int c1, int c2, uint32_t bar) {
  asm volatile("cp.async.bulk.tensor.3d.shared::cta.global.mbarrier::complete_tx::bytes [%0], [%1, {%3, %4, %5}], [%2];"
               :: "r"(dst), "l"(tm), "r"(bar), "r"(c0), "r"(c1), "r"(c2) : "memory");
}
__device__ __forceinline__ void tma_prefetch_desc(const CUtensorMap* tm) { asm volatile("prefetch.tensormap [%0];" :: "l"(tm) : "memory"); }

__device__ __forceinline__ void wgmma_fence() { asm volatile("wgmma.fence.sync.aligned;" ::: "memory"); }
__device__ __forceinline__ void wgmma_commit() { asm volatile("wgmma.commit_group.sync.aligned;" ::: "memory"); }
template <int N> __device__ __forceinline__ void wgmma_wait() { asm volatile("wgmma.wait_group.sync.aligned %0;" :: "n"(N) : "memory"); }
__device__ __forceinline__ uint64_t make_desc(uint32_t addr, uint32_t lbo_bytes, uint32_t sbo_bytes, uint32_t swz) {
  return (uint64_t)((addr & 0x3FFFF) >> 4) | ((uint64_t)((lbo_bytes & 0x3FFFF) >> 4) << 16) |
         ((uint64_t)((sbo_bytes & 0x3FFFF) >> 4) << 32) | ((uint64_t)swz << 62);
}
template <int NREG> __device__ __forceinline__ void reg_fence(float (&d)[NREG]) {
#pragma unroll
  for (int i = 0; i < NREG; i++) asm volatile("" : "+f"(d[i]) :: "memory");
}
__device__ __forceinline__ void mma16816(float (&c)[4], const uint32_t (&a)[4], uint32_t b0, uint32_t b1) {
  asm volatile("mma.sync.aligned.m16n8k16.row.col.f32.bf16.bf16.f32 {%0,%1,%2,%3}, {%4,%5,%6,%7}, {%8,%9}, {%0,%1,%2,%3};"
               : "+f"(c[0]), "+f"(c[1]), "+f"(c[2]), "+f"(c[3])
               : "r"(a[0]), "r"(a[1]), "r"(a[2]), "r"(a[3]), "r"(b0), "r"(b1));
}
__device__ __forceinline__ uint32_t movmatrix_t(uint32_t v) {
  uint32_t r; asm volatile("movmatrix.sync.aligned.m8n8.trans.b16 %0, %1;" : "=r"(r) : "r"(v)); return r;
}
__device__ __forceinline__ void ldsm_x4(uint32_t (&r)[4], uint32_t addr) {
  asm volatile("ldmatrix.sync.aligned.m8n8.x4.shared.b16 {%0,%1,%2,%3}, [%4];" : "=r"(r[0]), "=r"(r[1]), "=r"(r[2]), "=r"(r[3]) : "r"(addr) : "memory");
}
__device__ __forceinline__ void ldsm_x4_t(uint32_t (&r)[4], uint32_t addr) {
  asm volatile("ldmatrix.sync.aligned.m8n8.x4.trans.shared.b16 {%0,%1,%2,%3}, [%4];" : "=r"(r[0]), "=r"(r[1]), "=r"(r[2]), "=r"(r[3]) : "r"(addr) : "memory");
}

__device__ __forceinline__ void wgmma_rs_n32(float (&d)[16], const uint32_t (&a)[4], uint64_t db, int scale_d) {
  asm volatile("{\n.reg .pred p;\nsetp.ne.b32 p, %21, 0;\n"
    "wgmma.mma_async.sync.aligned.m64n32k16.f32.bf16.bf16 "
    "{%0, %1, %2, %3, %4, %5, %6, %7, %8, %9, %10, %11, %12, %13, %14, %15}, "
    "{%16, %17, %18, %19}, %20, p, 1, 1, 0;\n}\n"
    : "+f"(d[0]), "+f"(d[1]), "+f"(d[2]), "+f"(d[3]), "+f"(d[4]), "+f"(d[5]), "+f"(d[6]), "+f"(d[7]), "+f"(d[8]), "+f"(d[9]), "+f"(d[10]), "+f"(d[11]), "+f"(d[12]), "+f"(d[13]), "+f"(d[14]), "+f"(d[15])
    : "r"(a[0]), "r"(a[1]), "r"(a[2]), "r"(a[3]), "l"(db), "r"(scale_d));
}
__device__ __forceinline__ void wgmma_ss_n160_tb(float (&d)[80], uint64_t da, uint64_t db, int scale_d) {
  asm volatile("{\n.reg .pred p;\nsetp.ne.b32 p, %82, 0;\n"
    "wgmma.mma_async.sync.aligned.m64n160k16.f32.bf16.bf16 "
    "{%0, %1, %2, %3, %4, %5, %6, %7, %8, %9, %10, %11, %12, %13, %14, %15, %16, %17, %18, %19, %20, %21, %22, %23, %24, %25, %26, %27, %28, %29, %30, %31, %32, %33, %34, %35, %36, %37, %38, %39, %40, %41, %42, %43, %44, %45, %46, %47, %48, %49, %50, %51, %52, %53, %54, %55, %56, %57, %58, %59, %60, %61, %62, %63, %64, %65, %66, %67, %68, %69, %70, %71, %72, %73, %74, %75, %76, %77, %78, %79}, "
    "%80, %81, p, 1, 1, 0, 1;\n}\n"
    : "+f"(d[0]), "+f"(d[1]), "+f"(d[2]), "+f"(d[3]), "+f"(d[4]), "+f"(d[5]), "+f"(d[6]), "+f"(d[7]), "+f"(d[8]), "+f"(d[9]), "+f"(d[10]), "+f"(d[11]), "+f"(d[12]), "+f"(d[13]), "+f"(d[14]), "+f"(d[15]), "+f"(d[16]), "+f"(d[17]), "+f"(d[18]), "+f"(d[19]), "+f"(d[20]), "+f"(d[21]), "+f"(d[22]), "+f"(d[23]), "+f"(d[24]), "+f"(d[25]), "+f"(d[26]), "+f"(d[27]), "+f"(d[28]), "+f"(d[29]), "+f"(d[30]), "+f"(d[31]), "+f"(d[32]), "+f"(d[33]), "+f"(d[34]), "+f"(d[35]), "+f"(d[36]), "+f"(d[37]), "+f"(d[38]), "+f"(d[39]), "+f"(d[40]), "+f"(d[41]), "+f"(d[42]), "+f"(d[43]), "+f"(d[44]), "+f"(d[45]), "+f"(d[46]), "+f"(d[47]), "+f"(d[48]), "+f"(d[49]), "+f"(d[50]), "+f"(d[51]), "+f"(d[52]), "+f"(d[53]), "+f"(d[54]), "+f"(d[55]), "+f"(d[56]), "+f"(d[57]), "+f"(d[58]), "+f"(d[59]), "+f"(d[60]), "+f"(d[61]), "+f"(d[62]), "+f"(d[63]), "+f"(d[64]), "+f"(d[65]), "+f"(d[66]), "+f"(d[67]), "+f"(d[68]), "+f"(d[69]), "+f"(d[70]), "+f"(d[71]), "+f"(d[72]), "+f"(d[73]), "+f"(d[74]), "+f"(d[75]), "+f"(d[76]), "+f"(d[77]), "+f"(d[78]), "+f"(d[79])
    : "l"(da), "l"(db), "r"(scale_d));
}

__device__ bf16 g_Qp[A_H * S_LEN * 32];
__device__ bf16 g_Kp[A_H * S_LEN * 32];
__device__ bf16 g_Vt[A_H * 24 * S_LEN];
__device__ float g_kmax2[16 * A_H];
__device__ bf16 g_aA[S_LEN * DM];
__device__ bf16 g_oB[S_LEN * B_HD];

constexpr int GEMM_THREADS = 288;
constexpr int GEMM_BN = 160;
constexpr int GEMM_A_BYTES = 128 * 128;
constexpr int GEMM_B_BYTES = 5 * 4096;
constexpr int GEMM_STAGE = GEMM_A_BYTES + GEMM_B_BYTES;
enum { EPI_QKV = 0, EPI_OUT = 1 };
constexpr int EPI_PITCH = 336;

template <int EPI, int STAGES, int MINB>
__global__ void __launch_bounds__(GEMM_THREADS, MINB)
gemm_kernel(const __grid_constant__ CUtensorMap tmA, const __grid_constant__ CUtensorMap tmB, int K, bf16* __restrict__ out, int out_col0) {
  extern __shared__ uint8_t smem_raw[];
  const uint32_t sbase = (smem_u32(smem_raw) + 1023) & ~1023u;
  uint8_t* sgen = smem_raw + (sbase - smem_u32(smem_raw));
  __shared__ __align__(8) uint64_t s_full[STAGES], s_empty[STAGES];
  __shared__ unsigned s_kmax[8];
  const int tid = threadIdx.x, warp = tid >> 5, lane = tid & 31;
  const int n_tile = blockIdx.x, m_tile = blockIdx.y;
  const int nk = K / 64;
  if (tid == 0) {
    for (int i = 0; i < STAGES; i++) { mbar_init(smem_u32(&s_full[i]), 1); mbar_init(smem_u32(&s_empty[i]), 2); }
    fence_mbar_init();
  }
  if (tid < 8) s_kmax[tid] = 0;
  __syncthreads();
  if (warp == 8) {
    if (lane == 0) {
      for (int k = 0; k < nk; k++) {
        const int st = k % STAGES;
        if (k >= STAGES) mbar_wait(smem_u32(&s_empty[st]), ((k / STAGES) - 1) & 1);
        const uint32_t fb = smem_u32(&s_full[st]), sa = sbase + st * GEMM_STAGE;
        mbar_expect_tx(fb, GEMM_STAGE);
        tma_load_2d(sa, &tmA, k * 64, m_tile * 128, fb);
#pragma unroll
        for (int b = 0; b < 5; b++) tma_load_2d(sa + GEMM_A_BYTES + b * 4096, &tmB, n_tile * GEMM_BN + b * 32, k * 64, fb);
      }
    }
    return;
  }
  const int wg = warp >> 2;
  float acc[80];
  const uint64_t dA0 = make_desc(sbase + wg * 8192, 16, 1024, 1), dB0 = make_desc(sbase + GEMM_A_BYTES, 4096, 512, 2);
  for (int k = 0; k < nk; k++) {
    const int st = k % STAGES;
    mbar_wait(smem_u32(&s_full[st]), (k / STAGES) & 1);
    const uint64_t dA = dA0 + st * (GEMM_STAGE >> 4), dB = dB0 + st * (GEMM_STAGE >> 4);
    wgmma_fence();
#pragma unroll
    for (int kk = 0; kk < 4; kk++) wgmma_ss_n160_tb(acc, dA + kk * 2, dB + kk * 64, (k > 0 || kk > 0) ? 1 : 0);
    wgmma_commit();
    if (k > 0) {
      wgmma_wait<1>();
      if ((tid & 127) == 0) mbar_arrive(smem_u32(&s_empty[(k - 1) % STAGES]));
    }
  }
  wgmma_wait<0>();
  reg_fence(acc);
  bar_sync(1, 256);

  const int g = lane >> 2, t = lane & 3;
  const int lrow = wg * 64 + (warp & 3) * 16 + g;
  const int sec = (EPI == EPI_QKV) ? (n_tile >> 2) : 0;
  if (EPI == EPI_OUT || sec < 2) {
#pragma unroll
    for (int j = 0; j < 20; j++) {
      *(uint32_t*)(sgen + lrow * EPI_PITCH + (8 * j + 2 * t) * 2) = pack_bf16(acc[4 * j], acc[4 * j + 1]);
      *(uint32_t*)(sgen + (lrow + 8) * EPI_PITCH + (8 * j + 2 * t) * 2) = pack_bf16(acc[4 * j + 2], acc[4 * j + 3]);
    }
    bar_sync(1, 256);
    if (EPI == EPI_OUT) {
      for (int i = tid; i < 128 * 20; i += 256) {
        const int r = i / 20, c = i - r * 20;
        const uint4 v = *(const uint4*)(sgen + r * EPI_PITCH + c * 16);
        *(uint4*)(out + (size_t)(m_tile * 128 + r) * OUT_LD + out_col0 + n_tile * GEMM_BN + c * 8) = v;
      }
    } else {
      const int h0 = (n_tile & 3) * 8, pc = tid & 3;
      bf16* dst = (sec == 0 ? g_Qp : g_Kp);
      const uint32_t aug = (sec == 1) ? 0x3F803F80u : 0u;
#pragma unroll 1
      for (int hh = 0; hh < 8; hh++) {
        float mx = 0.f;
#pragma unroll
        for (int hf = 0; hf < 2; hf++) {
          const int r = hf * 64 + (tid >> 2);
          const uint8_t* src = sgen + r * EPI_PITCH + hh * 40 + pc * 16;
          uint4 v = make_uint4(0u, 0u, 0u, 0u);
          if (pc < 3) { const uint2 a = *(const uint2*)src; v.x = a.x; v.y = a.y; }
          if (pc < 2) { const uint2 b = *(const uint2*)(src + 8); v.z = b.x; v.w = b.y; }
          if (sec == 1) {
            float ss = bf16lo(v.x) * bf16lo(v.x) + bf16hi(v.x) * bf16hi(v.x) + bf16lo(v.y) * bf16lo(v.y) + bf16hi(v.y) * bf16hi(v.y)
                     + bf16lo(v.z) * bf16lo(v.z) + bf16hi(v.z) * bf16hi(v.z) + bf16lo(v.w) * bf16lo(v.w) + bf16hi(v.w) * bf16hi(v.w);
            ss += __shfl_xor_sync(~0u, ss, 1); ss += __shfl_xor_sync(~0u, ss, 2);
            if (!(ss == ss)) ss = __uint_as_float(0x7F800000u);
            mx = fmaxf(mx, ss);
          }
          if (pc == 2) v.z = aug;
          *(uint4*)(dst + ((size_t)(h0 + hh) * S_LEN + m_tile * 128 + r) * 32 + pc * 8) = v;
        }
        if (sec == 1) {
          mx = fmaxf(mx, __shfl_xor_sync(~0u, mx, 4)); mx = fmaxf(mx, __shfl_xor_sync(~0u, mx, 8)); mx = fmaxf(mx, __shfl_xor_sync(~0u, mx, 16));
          if (lane == 0) atomicMax(&s_kmax[hh], __float_as_uint(mx));
        }
      }
      if (sec == 1) {
        bar_sync(1, 256);
        if (tid < 8) g_kmax2[m_tile * A_H + h0 + tid] = __uint_as_float(s_kmax[tid]);
      }
    }
  } else {
    constexpr int VP = 272;
    const int ltok = wg * 64 + (warp & 3) * 16 + 2 * t;
#pragma unroll
    for (int j = 0; j < 20; j++) {
      *(uint32_t*)(sgen + (8 * j + g) * VP + ltok * 2) = movmatrix_t(pack_bf16(acc[4 * j], acc[4 * j + 1]));
      *(uint32_t*)(sgen + (8 * j + g) * VP + (ltok + 8) * 2) = movmatrix_t(pack_bf16(acc[4 * j + 2], acc[4 * j + 3]));
    }
    bar_sync(1, 256);
    const int h0 = (n_tile & 3) * 8;
    for (int i = tid; i < 8 * 24 * 16; i += 256) {
      const int ch = i & 15, rr = i >> 4, hh = rr / 24, d = rr - hh * 24;
      uint4 v;
      if (d < 20) v = *(const uint4*)(sgen + (hh * 20 + d) * VP + ch * 16);
      else { const uint32_t val = (d == 20) ? 0x3F803F80u : 0u; v = make_uint4(val, val, val, val); }
      *(uint4*)(g_Vt + ((size_t)(h0 + hh) * 24 + d) * S_LEN + m_tile * 128 + ch * 8) = v;
    }
  }
}

constexpr int ATT_STAGES = 6;
constexpr int ATT_LAG = 2;
constexpr int ATT_STAGE_BYTES = 8192 + 6144;
constexpr int ATT_SMEM = ATT_STAGES * ATT_STAGE_BYTES + 1024;
constexpr float A_SCALE_LOG2E = 0.22360679774997896f * 1.4426950408889634f;

__device__ __forceinline__ uint32_t bf16_up_bits(float x) {
  uint32_t u = __float_as_uint(x);
  if ((u & 0x7F800000u) == 0x7F800000u) return u >> 16;
  uint32_t r = (u & 0x80000000u) ? u : u + 0xFFFFu;
  return r >> 16;
}
__device__ __forceinline__ void mma16816_z(float (&d)[4], const uint32_t (&a)[4], uint32_t b0, uint32_t b1) {
  asm volatile("mma.sync.aligned.m16n8k16.row.col.f32.bf16.bf16.f32 {%0,%1,%2,%3}, {%4,%5,%6,%7}, {%8,%9}, {%10,%10,%10,%10};"
               : "=f"(d[0]), "=f"(d[1]), "=f"(d[2]), "=f"(d[3])
               : "r"(a[0]), "r"(a[1]), "r"(a[2]), "r"(a[3]), "r"(b0), "r"(b1), "f"(0.f));
}

__global__ void __launch_bounds__(256, 2)
attnA_kernel(const __grid_constant__ CUtensorMap tmK, const __grid_constant__ CUtensorMap tmV) {
  extern __shared__ uint8_t smem_raw[];
  const uint32_t sbase = (smem_u32(smem_raw) + 1023) & ~1023u;
  __shared__ __align__(8) uint64_t s_full[ATT_STAGES], s_empty[ATT_STAGES];
  __shared__ unsigned s_fail;
  const int tid = threadIdx.x, warp = tid >> 5, lane = tid & 31;
  const int qt = blockIdx.x & 7, h = blockIdx.x >> 3;
  if (tid == 0) {
    for (int i = 0; i < ATT_STAGES; i++) { mbar_init(smem_u32(&s_full[i]), 1); mbar_init(smem_u32(&s_empty[i]), 8); }
    s_fail = 0;
    fence_mbar_init();
  }
  __syncthreads();
  int issued = 0;
  auto refill = [&](int lim) {
    if (tid == 0) {
      for (; issued < lim; issued++) {
        const int st = issued % ATT_STAGES, j = issued & 15;
        const uint32_t fb = smem_u32(&s_full[st]), sa = sbase + st * ATT_STAGE_BYTES;
        if (issued >= ATT_STAGES) mbar_wait(smem_u32(&s_empty[st]), ((issued / ATT_STAGES) - 1) & 1);
        mbar_expect_tx(fb, ATT_STAGE_BYTES);
        tma_load_2d(sa, &tmK, 0, h * S_LEN + j * 128, fb);
        tma_load_2d(sa + 8192, &tmV, j * 128, h * 24, fb);
        tma_load_2d(sa + 8192 + 3072, &tmV, j * 128 + 64, h * 24, fb);
      }
    }
    __syncwarp();
  };
  refill(ATT_STAGES);

  const int g = lane >> 2, t = lane & 3;
  const int row0 = qt * 256 + warp * 32 + g;
  uint32_t qa[2][2][4];
#pragma unroll
  for (int m = 0; m < 2; m++) {
    const bf16* q0 = g_Qp + ((size_t)h * S_LEN + row0 + 16 * m) * 32 + 2 * t;
#pragma unroll
    for (int ks = 0; ks < 2; ks++) {
      qa[m][ks][0] = *(const uint32_t*)(q0 + 16 * ks);
      qa[m][ks][1] = *(const uint32_t*)(q0 + 16 * ks + 8 * 32);
      qa[m][ks][2] = *(const uint32_t*)(q0 + 16 * ks + 8);
      qa[m][ks][3] = *(const uint32_t*)(q0 + 16 * ks + 8 + 8 * 32);
    }
  }
  {
    float km = 0.f;
#pragma unroll
    for (int i = 0; i < 16; i++) { const float v = g_kmax2[i * A_H + h]; km = (v > km || !(v == v)) ? v : km; }
#pragma unroll
    for (int m = 0; m < 2; m++) {
      float n0 = 0.f, n1 = 0.f;
#pragma unroll
      for (int ks = 0; ks < 2; ks++) {
        const uint32_t* a = qa[m][ks];
        n0 += bf16lo(a[0]) * bf16lo(a[0]) + bf16hi(a[0]) * bf16hi(a[0]) + bf16lo(a[2]) * bf16lo(a[2]) + bf16hi(a[2]) * bf16hi(a[2]);
        n1 += bf16lo(a[1]) * bf16lo(a[1]) + bf16hi(a[1]) * bf16hi(a[1]) + bf16lo(a[3]) * bf16lo(a[3]) + bf16hi(a[3]) * bf16hi(a[3]);
      }
      n0 += __shfl_xor_sync(~0u, n0, 1); n0 += __shfl_xor_sync(~0u, n0, 2);
      n1 += __shfl_xor_sync(~0u, n1, 1); n1 += __shfl_xor_sync(~0u, n1, 2);
      const float b0 = sqrtf(n0 * km) * 1.0078125f, b1 = sqrtf(n1 * km) * 1.0078125f;
      if (t == 2) {
        qa[m][1][0] = bf16_up_bits(b0) | 0x8000u;
        qa[m][1][1] = bf16_up_bits(b1) | 0x8000u;
      }
    }
  }
  const uint32_t koff = (lane & 7) * 64 + (((lane >> 3) ^ ((lane & 7) >> 1)) << 4);
  const uint32_t voff0 = 8192 + (lane & 7) * 128 + ((((lane >> 3)) ^ (lane & 7)) << 4);
  const uint32_t voff1 = 8192 + (lane & 7) * 128 + (((4 + (lane >> 3)) ^ (lane & 7)) << 4);
  auto scores = [&](float (&s)[2][4][4], uint32_t kaddr) {
#pragma unroll
    for (int nt = 0; nt < 4; nt++) {
      uint32_t kb[4];
      ldsm_x4(kb, kaddr + nt * 512);
#pragma unroll
      for (int m = 0; m < 2; m++) { mma16816_z(s[m][nt], qa[m][0], kb[0], kb[1]); mma16816(s[m][nt], qa[m][1], kb[2], kb[3]); }
    }
  };
  auto release = [&](int stage_it) { __syncwarp(); if (lane == 0) mbar_arrive(smem_u32(&s_empty[stage_it % ATT_STAGES])); };

  int it = 0;
#pragma unroll 1
  for (int rep = 0; rep < 2; rep++) {
    float o[2][3][4];
#pragma unroll
    for (int m = 0; m < 2; m++)
#pragma unroll
      for (int d = 0; d < 3; d++) { o[m][d][0] = 0.f; o[m][d][1] = 0.f; o[m][d][2] = 0.f; o[m][d][3] = 0.f; }
    const int end_it = it + 16;
#pragma unroll 1
    for (; it < end_it; it++) {
      const uint32_t sa = sbase + (it % ATT_STAGES) * ATT_STAGE_BYTES;
      mbar_wait(smem_u32(&s_full[it % ATT_STAGES]), (it / ATT_STAGES) & 1);
#pragma unroll
      for (int q = 0; q < 4; q++) {
        float s[2][4][4];
        scores(s, sa + koff + q * 2048);
        uint32_t p[2][2][4];
        constexpr float SC = A_SCALE_LOG2E;
#pragma unroll
        for (int m = 0; m < 2; m++)
#pragma unroll
          for (int ks = 0; ks < 2; ks++) {
            p[m][ks][0] = pack_bf16(ex2f(s[m][2 * ks][0] * SC), ex2f(s[m][2 * ks][1] * SC));
            p[m][ks][1] = pack_bf16(ex2f(s[m][2 * ks][2] * SC), ex2f(s[m][2 * ks][3] * SC));
            p[m][ks][2] = pack_bf16(ex2f(s[m][2 * ks + 1][0] * SC), ex2f(s[m][2 * ks + 1][1] * SC));
            p[m][ks][3] = pack_bf16(ex2f(s[m][2 * ks + 1][2] * SC), ex2f(s[m][2 * ks + 1][3] * SC));
          }
        const uint32_t va = sa + ((q & 1) ? voff1 : voff0) + (q >> 1) * 3072;
#pragma unroll
        for (int d = 0; d < 3; d++) {
          uint32_t vb[4];
          ldsm_x4(vb, va + d * 1024);
#pragma unroll
          for (int m = 0; m < 2; m++) { mma16816(o[m][d], p[m][0], vb[0], vb[1]); mma16816(o[m][d], p[m][1], vb[2], vb[3]); }
        }
      }
      release(it);
      refill(min(it + 1 - ATT_LAG + ATT_STAGES, end_it));
    }
    float l[2][2];
    bool bad = false;
#pragma unroll
    for (int m = 0; m < 2; m++) {
      l[m][0] = __shfl_sync(~0u, o[m][2][0], (lane & ~3) | 2);
      l[m][1] = __shfl_sync(~0u, o[m][2][2], (lane & ~3) | 2);
      bad = bad || !(l[m][0] >= 8.271806e-25f && l[m][0] <= 3.0e38f) || !(l[m][1] >= 8.271806e-25f && l[m][1] <= 3.0e38f);
    }
    bool redo = false;
    if (rep == 0) {
      if (bad) atomicOr(&s_fail, 1u);
      __syncthreads();
      redo = *(volatile unsigned*)&s_fail != 0;
    }
    if (!redo) {
#pragma unroll
      for (int m = 0; m < 2; m++) {
        const float i0 = 1.0f / l[m][0], i1 = 1.0f / l[m][1];
        bf16* o0 = g_aA + (size_t)(row0 + 16 * m) * DM + h * A_DH + 2 * t;
#pragma unroll
        for (int j = 0; j < 3; j++) {
          if (j < 2 || t < 2) {
            *(uint32_t*)(o0 + 8 * j) = pack_bf16(o[m][j][0] * i0, o[m][j][1] * i0);
            *(uint32_t*)(o0 + 8 * j + 8 * DM) = pack_bf16(o[m][j][2] * i1, o[m][j][3] * i1);
          }
        }
      }
      break;
    }
    if (t == 2) { qa[0][1][0] = 0u; qa[0][1][1] = 0u; qa[1][1][0] = 0u; qa[1][1][1] = 0u; }
    float mx[2][2] = {{-INFINITY, -INFINITY}, {-INFINITY, -INFINITY}};
    const int end_mx = it + 16;
    refill(min(it + ATT_STAGES - ATT_LAG, end_mx));
#pragma unroll 1
    for (; it < end_mx; it++) {
      const uint32_t sa = sbase + (it % ATT_STAGES) * ATT_STAGE_BYTES;
      mbar_wait(smem_u32(&s_full[it % ATT_STAGES]), (it / ATT_STAGES) & 1);
#pragma unroll 1
      for (int q = 0; q < 4; q++) {
        float s[2][4][4];
        scores(s, sa + koff + q * 2048);
#pragma unroll
        for (int m = 0; m < 2; m++)
#pragma unroll
          for (int nt = 0; nt < 4; nt++) {
            mx[m][0] = fmaxf(mx[m][0], fmaxf(s[m][nt][0], s[m][nt][1]));
            mx[m][1] = fmaxf(mx[m][1], fmaxf(s[m][nt][2], s[m][nt][3]));
          }
      }
      release(it);
      refill(min(it + 1 - ATT_LAG + ATT_STAGES, end_mx));
    }
#pragma unroll
    for (int m = 0; m < 2; m++)
#pragma unroll
      for (int r = 0; r < 2; r++) {
        float v = mx[m][r];
        v = fmaxf(v, __shfl_xor_sync(~0u, v, 1)); v = fmaxf(v, __shfl_xor_sync(~0u, v, 2));
        if (t == 2) {
          const uint32_t hi = pack_bf16(v, 0.f) & 0xFFFFu;
          const uint32_t lo = pack_bf16(v - bf16lo(hi), 0.f) & 0xFFFFu;
          qa[m][1][r] = (hi | (lo << 16)) ^ 0x80008000u;
        }
      }
    refill(min(it + ATT_STAGES - ATT_LAG, it + 16));
  }
}

constexpr int REC_THREADS = 384;
constexpr int REC_CTAS = 96;
constexpr int SM_WO = 0;
constexpr int SM_X = 57344;
constexpr int SM_KX = SM_X + 2 * 40960;
constexpr int SM_VX = SM_KX + 2 * 8192;
constexpr int SM_QX = SM_VX + 2 * 8192;
constexpr int SM_M = SM_QX + 2 * 8192;
constexpr int SM_G = SM_M + 10240;
constexpr int SM_S = SM_G + 2 * 6144;
constexpr int SM_O = SM_S + 4 * 8 * 56 * 4;
constexpr int SM_P = SM_O + 2048;
constexpr int SM_END = SM_P + 2 * 768;
constexpr int SM_WSTAGE = SM_X;
constexpr int REC_SMEM = (SM_WSTAGE + 163840 > SM_END ? SM_WSTAGE + 163840 : SM_END) + 1024;
constexpr float B_SCALE_LOG2E = 0.08838834764831845f * 1.4426950408889634f;

__device__ uint32_t g_part[REC_CTAS * 4 * 512];
__device__ uint32_t g_mem[4 * 2560];
__device__ unsigned g_gridbar;

enum { BAR_CMP = 1, BAR_P4 = 2, BAR_S = 5, BAR_XP = 6, BAR_WG1 = 7 };
#define TR(i)
#define TR1(i)

__device__ __forceinline__ uint32_t mapa_u32(uint32_t addr, uint32_t rank) { uint32_t r; asm("mapa.shared::cluster.u32 %0, %1, %2;" : "=r"(r) : "r"(addr), "r"(rank)); return r; }
__device__ __forceinline__ void st_async_v2(uint32_t raddr, uint32_t a, uint32_t b, uint32_t rbar) {
  asm volatile("st.async.weak.shared::cluster.mbarrier::complete_tx::bytes.v2.b32 [%0], {%1, %2}, [%3];" :: "r"(raddr), "r"(a), "r"(b), "r"(rbar) : "memory");
}
__device__ __forceinline__ void bulk_s2c(uint32_t dst, uint32_t src, uint32_t bytes, uint32_t rbar) {
  asm volatile("cp.async.bulk.shared::cluster.shared::cta.mbarrier::complete_tx::bytes [%0], [%1], %2, [%3];" :: "r"(dst), "r"(src), "r"(bytes), "r"(rbar) : "memory");
}
__device__ __forceinline__ uint4 ld_relaxed_v4(const void* p) { uint4 v; asm volatile("ld.relaxed.gpu.global.v4.u32 {%0,%1,%2,%3}, [%4];" : "=r"(v.x), "=r"(v.y), "=r"(v.z), "=r"(v.w) : "l"(p) : "memory"); return v; }
__device__ __forceinline__ uint32_t ld_relaxed(const void* p) { uint32_t v; asm volatile("ld.relaxed.gpu.global.u32 %0, [%1];" : "=r"(v) : "l"(p) : "memory"); return v; }
__device__ __forceinline__ void st_relaxed_v2(void* p, uint32_t a, uint32_t b) { asm volatile("st.relaxed.gpu.global.v2.u32 [%0], {%1,%2};" :: "l"(p), "r"(a), "r"(b) : "memory"); }
__device__ __forceinline__ void st_relaxed(void* p, uint32_t a) { asm volatile("st.relaxed.gpu.global.u32 [%0], %1;" :: "l"(p), "r"(a) : "memory"); }
__device__ __forceinline__ uint2 lds64(uint32_t a) { uint2 v; asm volatile("ld.shared.v2.u32 {%0,%1}, [%2];" : "=r"(v.x), "=r"(v.y) : "r"(a) : "memory"); return v; }
__device__ __forceinline__ void lds128(uint32_t (&r)[4], uint32_t a) { asm volatile("ld.shared.v4.u32 {%0,%1,%2,%3}, [%4];" : "=r"(r[0]), "=r"(r[1]), "=r"(r[2]), "=r"(r[3]) : "r"(a) : "memory"); }
__device__ __forceinline__ void sts64(uint32_t a, uint32_t x, uint32_t y) { asm volatile("st.shared.v2.u32 [%0], {%1,%2};" :: "r"(a), "r"(x), "r"(y) : "memory"); }
__device__ __forceinline__ void sts128(uint32_t a, uint32_t x, uint32_t y, uint32_t z, uint32_t w) { asm volatile("st.shared.v4.u32 [%0], {%1,%2,%3,%4};" :: "r"(a), "r"(x), "r"(y), "r"(z), "r"(w) : "memory"); }
__device__ __forceinline__ void sts32f(uint32_t a, float x) { asm volatile("st.shared.f32 [%0], %1;" :: "r"(a), "f"(x) : "memory"); }
__device__ __forceinline__ float2 lds64f(uint32_t a) { float2 v; asm volatile("ld.shared.v2.f32 {%0,%1}, [%2];" : "=f"(v.x), "=f"(v.y) : "r"(a) : "memory"); return v; }

#define REC_DELAY_A 200
#define REC_DELAY_C 350
constexpr uint32_t POLL_LIMIT = 1u << 16;
__device__ __forceinline__ uint32_t umin4(const uint4& v) { return min(min(v.x, v.y), min(v.z, v.w)); }
__device__ __forceinline__ void spin_clocks(uint32_t clks) {
  uint32_t t0, t1;
  asm volatile("mov.u32 %0, %%clock;" : "=r"(t0) :: "memory");
  do { asm volatile("mov.u32 %0, %%clock;" : "=r"(t1) :: "memory"); } while (t1 - t0 < clks);
}
__device__ __forceinline__ int rw_mailbox(int rw) { const int c = rw / 10, o = rw - c * 10; return (o < 4) ? (c * 3) * 4 + o : (o < 7 ? (c * 3 + 1) * 4 + (o - 4) : (c * 3 + 2) * 4 + (o - 7)); }

struct ScoreAddr { uint32_t lo, lo_stride, hi, hi_mask; };
__device__ __forceinline__ ScoreAddr score_addr(int mt, uint32_t km_addr, uint32_t kx_addr, int lane) {
  ScoreAddr r;
  r.lo = (mt == 0 ? km_addr : kx_addr + (mt == 1 ? 256 : 768)) + lane * 8;
  r.lo_stride = (mt == 0) ? 256 : 1024;
  r.hi = kx_addr + (mt == 1 ? 512 : 0) + lane * 8;
  r.hi_mask = (mt == 2) ? 0u : 0xFFFFFFFFu;
  return r;
}
__device__ __forceinline__ void score_finish(const uint2 (&lo)[8], const uint2 (&hi)[8], uint32_t q_addr, int mt, uint32_t s_addr, int lane) {
  float c[4][4];
  uint2 q[8];
#pragma unroll
  for (int ks = 0; ks < 8; ks++) q[ks] = lds64(q_addr + ks * 256 + lane * 8);
#pragma unroll
  for (int i = 0; i < 4; i++) { c[i][0] = 0.f; c[i][1] = 0.f; c[i][2] = 0.f; c[i][3] = 0.f; }
#pragma unroll
  for (int ks = 0; ks < 8; ks++) {
    const uint32_t a[4] = {lo[ks].x, hi[ks].x, lo[ks].y, hi[ks].y};
    mma16816(c[ks & 3], a, q[ks].x, q[ks].y);
  }
  const int g = lane >> 2, t = lane & 3;
  const uint32_t d = s_addr + ((2 * t) * 56 + 16 * mt + g) * 4;
  sts32f(d, (c[0][0] + c[1][0]) + (c[2][0] + c[3][0])); sts32f(d + 56 * 4, (c[0][1] + c[1][1]) + (c[2][1] + c[3][1]));
  sts32f(d + 32, (c[0][2] + c[1][2]) + (c[2][2] + c[3][2])); sts32f(d + 56 * 4 + 32, (c[0][3] + c[1][3]) + (c[2][3] + c[3][3]));
}
__device__ __forceinline__ void rec_scores(int mt, uint32_t km_addr, uint32_t kx_addr, uint32_t q_addr, uint32_t s_addr, int lane) {
  const ScoreAddr sa = score_addr(mt, km_addr, kx_addr, lane);
  uint2 lo[8], hi[8];
#pragma unroll
  for (int ks = 0; ks < 8; ks++) {
    lo[ks] = lds64(sa.lo + ks * sa.lo_stride);
    hi[ks] = lds64(sa.hi + ks * 1024);
    hi[ks].x &= sa.hi_mask; hi[ks].y &= sa.hi_mask;
  }
  score_finish(lo, hi, q_addr, mt, s_addr, lane);
}
template <int U>
__device__ __forceinline__ void rec_softmax(uint32_t (&pb)[U][5], float (&inv)[U], const uint32_t (&s_addr)[U], const int (&lim)[U], int lane) {
  const int g = lane >> 2, t = lane & 3;
  float v[U][10], m[U];
#pragma unroll
  for (int u = 0; u < U; u++)
#pragma unroll
    for (int i = 0; i < 5; i++) {
      const float2 x = lds64f(s_addr[u] + (g * 56 + 8 * i + 2 * t) * 4);
      v[u][2 * i] = (8 * i + 2 * t <= lim[u]) ? x.x : -INFINITY;
      v[u][2 * i + 1] = (8 * i + 2 * t + 1 <= lim[u]) ? x.y : -INFINITY;
    }
#pragma unroll
  for (int u = 0; u < U; u++)
    m[u] = fmaxf(fmaxf(fmaxf(fmaxf(v[u][0], v[u][1]), fmaxf(v[u][2], v[u][3])), fmaxf(fmaxf(v[u][4], v[u][5]), fmaxf(v[u][6], v[u][7]))), fmaxf(v[u][8], v[u][9]));
#pragma unroll
  for (int u = 0; u < U; u++) m[u] = fmaxf(m[u], __shfl_xor_sync(~0u, m[u], 1));
#pragma unroll
  for (int u = 0; u < U; u++) m[u] = fmaxf(m[u], __shfl_xor_sync(~0u, m[u], 2)) * B_SCALE_LOG2E;
#pragma unroll
  for (int u = 0; u < U; u++) {
#pragma unroll
    for (int i = 0; i < 10; i++) v[u][i] = ex2f(fmaf(v[u][i], B_SCALE_LOG2E, -m[u]));
#pragma unroll
    for (int i = 0; i < 5; i++) pb[u][i] = pack_bf16(v[u][2 * i], v[u][2 * i + 1]);
  }
#pragma unroll
  for (int u = 0; u < U; u++) {
    float x[5];
#pragma unroll
    for (int i = 0; i < 5; i++) x[i] = bf16lo(pb[u][i]) + bf16hi(pb[u][i]);
    inv[u] = ((x[0] + x[1]) + (x[2] + x[3])) + x[4];
  }
#pragma unroll
  for (int u = 0; u < U; u++) inv[u] += __shfl_xor_sync(~0u, inv[u], 1);
#pragma unroll
  for (int u = 0; u < U; u++) { inv[u] += __shfl_xor_sync(~0u, inv[u], 2); asm("rcp.approx.ftz.f32 %0, %0;" : "+f"(inv[u])); }
}
__device__ __forceinline__ void rec_pv(uint32_t& o0, uint32_t& o1, uint2 vm, const uint2 (&vx)[4], const uint32_t (&pb)[5], float ia, float ib) {
  float c[4] = {0.f, 0.f, 0.f, 0.f}, e[4] = {0.f, 0.f, 0.f, 0.f};
  { const uint32_t a[4] = {vx[1].x, vx[1].y, vx[2].x, vx[2].y}; mma16816(e, a, pb[2], pb[3]); }
  { const uint32_t a[4] = {vx[3].x, vx[3].y, 0u, 0u}; mma16816(c, a, pb[4], 0u); }
  { const uint32_t a[4] = {vm.x, vm.y, vx[0].x, vx[0].y}; mma16816(c, a, pb[0], pb[1]); }
  o0 = movmatrix_t(pack_bf16((c[0] + e[0]) * ia, (c[1] + e[1]) * ib));
  o1 = movmatrix_t(pack_bf16((c[2] + e[2]) * ia, (c[3] + e[3]) * ib));
}

__global__ void __cluster_dims__(3, 1, 1) __launch_bounds__(REC_THREADS, 1)
rec_kernel(const __grid_constant__ CUtensorMap tmWq, const __grid_constant__ CUtensorMap tmWk, const __grid_constant__ CUtensorMap tmWv,
           const __grid_constant__ CUtensorMap tmWo, const __grid_constant__ CUtensorMap tmX, const bf16* __restrict__ mem0) {
  extern __shared__ uint8_t smem_raw[];
  const uint32_t sb = (smem_u32(smem_raw) + 1023) & ~1023u;
  __shared__ __align__(8) uint64_t s_bar[10];
  const uint32_t B_W = smem_u32(&s_bar[0]), B_WO = smem_u32(&s_bar[1]), B_M = smem_u32(&s_bar[2]), B_G = smem_u32(&s_bar[3]);
  const uint32_t B_KV = smem_u32(&s_bar[4])  , B_XF = smem_u32(&s_bar[6])  , B_XE = smem_u32(&s_bar[8])  ;
  const int tid = threadIdx.x, warp = tid >> 5, lane = tid & 31;
  uint32_t role; asm("mov.u32 %0, %%cluster_ctarank;" : "=r"(role));
  const int h = blockIdx.x / 3;
  const int tile0 = (role == 0) ? 0 : (role == 1 ? 14 : 27), ntile = (role == 0) ? 14 : 13;
  if (tid == 0) {
    mbar_init(B_W, 1); mbar_init(B_WO, 1); mbar_init(B_M, 4); mbar_init(B_G, 9);
    mbar_init(B_KV, 1); mbar_init(B_KV + 8, 1); mbar_init(B_XF, 1); mbar_init(B_XF + 8, 1); mbar_init(B_XE, 8); mbar_init(B_XE + 8, 8);
    fence_mbar_init();
  }
  __syncthreads();
  asm volatile("barrier.cluster.arrive.release.aligned;\nbarrier.cluster.wait.acquire.aligned;" ::: "memory");

  if (warp >= 8) {
    asm volatile("setmaxnreg.dec.sync.aligned.u32 40;");
    const int ct = tid - 256, cw = warp - 8;
    const int nw = (role == 0) ? 4 : 3;
    const int rw = h * 10 + (role == 0 ? 0 : (role == 1 ? 4 : 7)) + cw;
    if (ct == 0) {
      const CUtensorMap* tw = (role == 0) ? &tmWq : (role == 1 ? &tmWk : &tmWv);
      mbar_expect_tx(B_WO, 7 * 8192);
      for (int b = 0; b < 7; b++) tma_load_2d(sb + SM_WO + b * 8192, &tmWo, tile0 * 16 + b * 32, h * 128, B_WO);
      mbar_expect_tx(B_W, 163840);
      for (int c = 0; c < 10; c++) {
        tma_load_2d(sb + SM_WSTAGE + c * 16384, tw, h * 128, c * 64, B_W);
        tma_load_2d(sb + SM_WSTAGE + c * 16384 + 8192, tw, h * 128 + 64, c * 64, B_W);
      }
    }
    uint32_t* mbox = g_part + (blockIdx.x * 4 + cw) * 512;
    if (cw < nw) {
#pragma unroll
      for (int i = 0; i < 4; i++) *(uint4*)(mbox + (i * 32 + lane) * 4) = make_uint4(0u, 0u, 0u, 0u);
      if (lane < 8) g_mem[1 * 2560 + rw * 8 + lane] = 0u;
    }
    __threadfence();
    bar_sync(3, 128);
    if (ct == 0) {
      const unsigned old = atomicAdd(&g_gridbar, 1u);
      const unsigned target = (old / REC_CTAS + 1) * REC_CTAS;
      uint32_t n = 0;
      while ((int)(ld_relaxed(&g_gridbar) - target) < 0) { if (++n > (1u << 20)) { g_timeout_flag = 3; break; } }
      __threadfence();
    }
    for (int v = ct; v < 640; v += 128) {
      const uint4 x = *(const uint4*)(mem0 + (v & 7) * DM + (v >> 3) * 8);
      sts128(sb + SM_M + v * 16, x.x, x.y, x.z, x.w);
    }
    bar_sync(3, 128);
    if (lane == 0) mbar_arrive(B_M);
    bar_sync(4, REC_THREADS);
    if (ct == 0) {
      for (int i = 0; i < 2; i++) { mbar_expect_tx(B_XF + 8 * i, 40960); tma_load_3d(sb + SM_X + i * 40960, &tmX, 0, i * 32, 0, B_XF + 8 * i); }
    }
#pragma unroll 1
    for (int s = 0; s < B_NSEG; s++) {
      if (s > 0) {
        const uint4* src = (const uint4*)(g_mem + (s & 3) * 2560) + ct;
        uint4 v0, v1, v2, v3, v4;
        spin_clocks(REC_DELAY_A);
#pragma unroll 1
        for (uint32_t n = 0;; n++) {
          v0 = ld_relaxed_v4(src); v1 = ld_relaxed_v4(src + 128); v2 = ld_relaxed_v4(src + 256); v3 = ld_relaxed_v4(src + 384); v4 = ld_relaxed_v4(src + 512);
          const uint32_t m = min(min(min(umin4(v0), umin4(v1)), min(umin4(v2), umin4(v3))), umin4(v4));
          if (m != 0u) break;
          if (n > POLL_LIMIT) { g_timeout_flag = 4; break; }
        }
        const uint32_t dst = sb + SM_M + ct * 16;
        sts128(dst, ~v0.x, ~v0.y, ~v0.z, ~v0.w); sts128(dst + 2048, ~v1.x, ~v1.y, ~v1.z, ~v1.w); sts128(dst + 4096, ~v2.x, ~v2.y, ~v2.z, ~v2.w);
        sts128(dst + 6144, ~v3.x, ~v3.y, ~v3.z, ~v3.w); sts128(dst + 8192, ~v4.x, ~v4.y, ~v4.z, ~v4.w);
        __syncwarp();
        if (lane == 0) mbar_arrive(B_M);
        TR(9);
      }
      if (ct == 0 && s + 2 < B_NSEG) {
        mbar_wait(B_XE + 8 * (s & 1), (s >> 1) & 1);
        mbar_expect_tx(B_XF + 8 * (s & 1), 40960);
        tma_load_3d(sb + SM_X + (s & 1) * 40960, &tmX, 0, (s + 2) * 32, 0, B_XF + 8 * (s & 1));
      }
      if (s == B_NSEG - 1) break;
      if (cw < nw && lane < 8) st_relaxed(g_mem + ((s + 2) & 3) * 2560 + rw * 8 + lane, 0u);
      asm volatile("fence.acq_rel.gpu;" ::: "memory");
      TR(10);
      bar_sync(BAR_P4, REC_THREADS);
      if (cw < nw) {
        const uint4* src = (const uint4*)(g_part + (blockIdx.x * 4 + cw) * 512) + lane;
        const uint32_t flip = (s & 1) ? 0xFFFFFFFFu : 0u;
        uint4 v0, v1, v2, v3;
        spin_clocks(REC_DELAY_C);
        TR(11);
#pragma unroll 1
        for (uint32_t n = 0;; n++) {
          v0 = ld_relaxed_v4(src); v1 = ld_relaxed_v4(src + 32); v2 = ld_relaxed_v4(src + 64); v3 = ld_relaxed_v4(src + 96);
          const uint32_t a = ((v0.x ^ flip) & (v0.y ^ flip) & (v0.z ^ flip) & (v0.w ^ flip)) & ((v1.x ^ flip) & (v1.y ^ flip) & (v1.z ^ flip) & (v1.w ^ flip)) &
                             ((v2.x ^ flip) & (v2.y ^ flip) & (v2.z ^ flip) & (v2.w ^ flip)) & ((v3.x ^ flip) & (v3.y ^ flip) & (v3.z ^ flip) & (v3.w ^ flip));
          if (__all_sync(~0u, a & 1u)) break;
          if (n > POLL_LIMIT) { g_timeout_flag = 5; break; }
        }
        float f0 = (__uint_as_float(v0.x) + __uint_as_float(v1.x)) + (__uint_as_float(v2.x) + __uint_as_float(v3.x));
        float f1 = (__uint_as_float(v0.y) + __uint_as_float(v1.y)) + (__uint_as_float(v2.y) + __uint_as_float(v3.y));
        float f2 = (__uint_as_float(v0.z) + __uint_as_float(v1.z)) + (__uint_as_float(v2.z) + __uint_as_float(v3.z));
        float f3 = (__uint_as_float(v0.w) + __uint_as_float(v1.w)) + (__uint_as_float(v2.w) + __uint_as_float(v3.w));
#pragma unroll
        for (int o = 4; o < 32; o <<= 1) { f0 += __shfl_xor_sync(~0u, f0, o); f1 += __shfl_xor_sync(~0u, f1, o); f2 += __shfl_xor_sync(~0u, f2, o); f3 += __shfl_xor_sync(~0u, f3, o); }
        const uint32_t w = (lane & 4) ? pack_bf16(f1, f3) : pack_bf16(f0, f2);
        if (lane < 8) st_relaxed(g_mem + ((s + 1) & 3) * 2560 + rw * 8 + lane, ~w);
        TR(12);
      }
    }
  } else {
    asm volatile("setmaxnreg.inc.sync.aligned.u32 232;");
    const int g = lane >> 2, t = lane & 3;
    uint32_t W[40][4];
    {
      mbar_wait(B_WO, 0);
      uint32_t f[2][8][4];
#pragma unroll
      for (int q = 0; q < 2; q++) {
        const int i = min(warp + 8 * q, 13);
#pragma unroll
        for (int ks = 0; ks < 8; ks++) {
          const int e = ks * 16 + (lane & 7) + ((lane >> 4) & 1) * 8;
          const int ch = (i & 1) * 2 + ((lane >> 3) & 1);
          ldsm_x4_t(f[q][ks], sb + SM_WO + (i >> 1) * 8192 + e * 64 + ((ch ^ ((e >> 1) & 3)) << 4));
        }
      }
      bar_sync(BAR_CMP, 256);
#pragma unroll
      for (int q = 0; q < 2; q++) {
        const int i = warp + 8 * q;
        if (i < 14) {
#pragma unroll
          for (int ks = 0; ks < 8; ks++) sts128(sb + SM_WO + (i * 8 + ks) * 512 + lane * 16, f[q][ks][0], f[q][ks][1], f[q][ks][2], f[q][ks][3]);
        }
      }
    }
    mbar_wait(B_W, 0);
#pragma unroll
    for (int ks = 0; ks < 40; ks++) {
      const int k = (ks & 3) * 16 + (lane & 7) + ((lane >> 4) & 1) * 8;
      const int ch = (warp & 3) * 2 + ((lane >> 3) & 1);
      ldsm_x4_t(W[ks], sb + SM_WSTAGE + (ks >> 2) * 16384 + (warp >> 2) * 8192 + k * 128 + ((ch ^ (k & 7)) << 4));
    }
    bar_sync(4, REC_THREADS);

    const uint32_t peer0 = (role + 1) % 3, peer1 = (role + 2) % 3;
    const int mytile0 = (warp >= 4) ? warp - 4 : 8 + warp, mytile1 = (warp >= 4) ? warp : 12 + warp;
    const bool has_tile1 = mytile1 < ntile;
    uint32_t pdst[2][2];
#pragma unroll
    for (int q = 0; q < 2; q++)
#pragma unroll
      for (int hf = 0; hf < 2; hf++) {
        const int tile = tile0 + min(q ? mytile1 : mytile0, ntile - 1);
        const int rwd = (tile * 2 + hf) * 4 + t;
        pdst[q][hf] = rw_mailbox(rwd) * 512 + h * 16 + g * 2;
      }

    float d[16];
    auto bulk_issue = [&](int seg) {
      const int b = seg & 1;
      if (seg < B_NSEG) mbar_wait(B_XF + 8 * b, (seg >> 1) & 1);
      __syncwarp();
      const uint64_t dx = make_desc(sb + SM_X, 16, 1024, 1) + (uint64_t)(b * (40960 >> 4));
      wgmma_fence();
#pragma unroll
      for (int ks = 0; ks < 40; ks++) wgmma_rs_n32(d, W[ks], dx + (ks >> 2) * 256 + (ks & 3) * 2, ks > 0);
      wgmma_commit();
    };
    auto bulk_convert = [&](int seg) {
      const int b = seg & 1;
      __syncwarp();
      if (lane == 0) mbar_arrive(B_XE + 8 * b);
      const uint32_t dst = sb + (role == 0 ? SM_QX + warp * 256 : (role == 1 ? SM_KX : SM_VX) + warp * 1024) + b * 8192 + lane * 8;
      const uint32_t jstr = (role == 0) ? 2048 : 256;
#pragma unroll
      for (int j = 0; j < 4; j++) {
        uint32_t x0 = pack_bf16(d[4 * j], d[4 * j + 1]), x1 = pack_bf16(d[4 * j + 2], d[4 * j + 3]);
        if (role != 2) { x0 = movmatrix_t(x0); x1 = movmatrix_t(x1); }
        sts64(dst + j * jstr, x0, x1);
      }
      fence_proxy_async();
    };
    auto bulk_send = [&](int seg) {
      const int b = seg & 1;
      if (tid == 0) {
        mbar_expect_tx(B_KV + 8 * b, role == 0 ? 16384 : 8192 + 2048);
        if (role != 0) {
          const uint32_t src = sb + (role == 1 ? SM_KX : SM_VX) + b * 8192;
          bulk_s2c(mapa_u32(src, peer0), src, 8192, mapa_u32(B_KV + 8 * b, peer0));
          bulk_s2c(mapa_u32(src, peer1), src, 8192, mapa_u32(B_KV + 8 * b, peer1));
        } else {
          const uint32_t src = sb + SM_QX + b * 8192;
          bulk_s2c(mapa_u32(src + 2 * 2048, 1), src + 2 * 2048, 2048, mapa_u32(B_KV + 8 * b, 1));
          bulk_s2c(mapa_u32(src + 3 * 2048, 2), src + 3 * 2048, 2048, mapa_u32(B_KV + 8 * b, 2));
        }
      }
    };
    bulk_issue(0);
    wgmma_wait<0>();
    reg_fence(d);
    bulk_convert(0);
    bar_sync(BAR_CMP, 256);
    bulk_send(0);

#pragma unroll 1
    for (int s = 0; s < B_NSEG; s++) {
      const int b = s & 1;
      const uint32_t sG = sb + SM_G + b * 6144, sKX = sb + SM_KX + b * 8192, sVX = sb + SM_VX + b * 8192;
      if (tid == 0) mbar_expect_tx(B_G, 4096);
      TR(0);
      mbar_wait(B_M, s & 1);
      TR(1);
      {
        float c[4][4];
#pragma unroll
        for (int i = 0; i < 4; i++) { c[i][0] = 0.f; c[i][1] = 0.f; c[i][2] = 0.f; c[i][3] = 0.f; }
#pragma unroll
        for (int i = 0; i < 20; i++) {
          uint32_t mb[4];
          ldsm_x4(mb, sb + SM_M + i * 512 + lane * 16);
          mma16816(c[(2 * i) & 3], W[2 * i], mb[0], mb[1]);
          mma16816(c[(2 * i + 1) & 3], W[2 * i + 1], mb[2], mb[3]);
        }
        uint32_t x0 = pack_bf16(c[0][0] + c[1][0] + c[2][0] + c[3][0], c[0][1] + c[1][1] + c[2][1] + c[3][1]);
        uint32_t x1 = pack_bf16(c[0][2] + c[1][2] + c[2][2] + c[3][2], c[0][3] + c[1][3] + c[2][3] + c[3][3]);
        if (role != 2) { x0 = movmatrix_t(x0); x1 = movmatrix_t(x1); }
        const uint32_t off = sG + role * 2048 + warp * 256 + lane * 8;
        st_async_v2(mapa_u32(off, peer0), x0, x1, mapa_u32(B_G, peer0));
        st_async_v2(mapa_u32(off, peer1), x0, x1, mapa_u32(B_G, peer1));
        sts64(off, x0, x1);
        __syncwarp();
        if (lane == 0) mbar_arrive(B_G);
      }
      TR(2);
      mbar_wait(B_KV + 8 * b, (s >> 1) & 1);
      TR(3);
      const bool last = (s == B_NSEG - 1);
      const uint32_t tag = (s & 1) ^ 1;
      if (warp < 4) {
        uint2 vx[2][4], vm[2];
#pragma unroll
        for (int m = 0; m < 2; m++)
#pragma unroll
          for (int j = 0; j < 4; j++) vx[m][j] = lds64(sVX + (2 * warp + m) * 1024 + j * 256 + lane * 8);
        mbar_wait(B_G, s & 1);
        TR(4);
        if (!last) {
#pragma unroll
          for (int m = 0; m < 2; m++) vm[m] = lds64(sG + 2 * 2048 + (2 * warp + m) * 256 + lane * 8);
          bar_sync(BAR_S, 224);
          uint32_t pb[1][5]; float inv[1];
          { const uint32_t sa[1] = {sb + SM_S}; const int lim[1] = {39}; rec_softmax<1>(pb, inv, sa, lim, lane); }
          const float ia = __shfl_sync(~0u, inv[0], 8 * t), ib = __shfl_sync(~0u, inv[0], 8 * t + 4);
#pragma unroll
          for (int m = 0; m < 2; m++) {
            uint32_t o0, o1;
            rec_pv(o0, o1, vm[m], vx[m], pb[0], ia, ib);
            sts64(sb + SM_O + (2 * warp + m) * 256 + lane * 8, o0, o1);
          }
          bar_sync(BAR_CMP, 256);
          TR(5);
          uint2 ob[8];
#pragma unroll
          for (int ks = 0; ks < 8; ks++) ob[ks] = lds64(sb + SM_O + ks * 256 + lane * 8);
#pragma unroll
          for (int q = 0; q < 2; q++) {
            if (q == 0 ? (mytile0 < ntile) : has_tile1) {
              float c[2][4] = {{0.f, 0.f, 0.f, 0.f}, {0.f, 0.f, 0.f, 0.f}};
              uint32_t a[8][4];
#pragma unroll
              for (int ks = 0; ks < 8; ks++) lds128(a[ks], sb + SM_WO + ((q ? mytile1 : mytile0) * 8 + ks) * 512 + lane * 16);
#pragma unroll
              for (int ks = 0; ks < 8; ks++) mma16816(c[ks & 1], a[ks], ob[ks].x, ob[ks].y);
              st_relaxed_v2(g_part + pdst[q][0], (__float_as_uint(c[0][0] + c[1][0]) & ~1u) | tag, (__float_as_uint(c[0][1] + c[1][1]) & ~1u) | tag);
              st_relaxed_v2(g_part + pdst[q][1], (__float_as_uint(c[0][2] + c[1][2]) & ~1u) | tag, (__float_as_uint(c[0][3] + c[1][3]) & ~1u) | tag);
            }
          }
        }
      } else {
        const int mt = warp - 4;
        if (!last && mt < 3) {
          const ScoreAddr sa = score_addr(mt, sG + 2048, sKX, lane);
          uint2 lo[8], hi[8];
#pragma unroll
          for (int ks = 0; ks < 8; ks++) { hi[ks] = lds64(sa.hi + ks * 1024); hi[ks].x &= sa.hi_mask; hi[ks].y &= sa.hi_mask; }
          mbar_wait(B_G, s & 1);
#pragma unroll
          for (int ks = 0; ks < 8; ks++) lo[ks] = lds64(sa.lo + ks * sa.lo_stride);
          score_finish(lo, hi, sG, mt, sb + SM_S, lane);
          bar_arrive(BAR_S, 224);
        } else {
          mbar_wait(B_G, s & 1);
        }
        if (!last) {
          uint32_t a0[8][4];
#pragma unroll
          for (int ks = 0; ks < 8; ks++) lds128(a0[ks], sb + SM_WO + (mytile0 * 8 + ks) * 512 + lane * 16);
          bar_sync(BAR_CMP, 256);
          uint2 ob[8];
#pragma unroll
          for (int ks = 0; ks < 8; ks++) ob[ks] = lds64(sb + SM_O + ks * 256 + lane * 8);
          {
            float c[2][4] = {{0.f, 0.f, 0.f, 0.f}, {0.f, 0.f, 0.f, 0.f}};
#pragma unroll
            for (int ks = 0; ks < 8; ks++) mma16816(c[ks & 1], a0[ks], ob[ks].x, ob[ks].y);
            st_relaxed_v2(g_part + pdst[0][0], (__float_as_uint(c[0][0] + c[1][0]) & ~1u) | tag, (__float_as_uint(c[0][1] + c[1][1]) & ~1u) | tag);
            st_relaxed_v2(g_part + pdst[0][1], (__float_as_uint(c[0][2] + c[1][2]) & ~1u) | tag, (__float_as_uint(c[0][3] + c[1][3]) & ~1u) | tag);
          }
          {
            float c[2][4] = {{0.f, 0.f, 0.f, 0.f}, {0.f, 0.f, 0.f, 0.f}};
#pragma unroll
            for (int ks = 0; ks < 8; ks++) lds128(a0[ks], sb + SM_WO + (mytile1 * 8 + ks) * 512 + lane * 16);
#pragma unroll
            for (int ks = 0; ks < 8; ks++) mma16816(c[ks & 1], a0[ks], ob[ks].x, ob[ks].y);
            st_relaxed_v2(g_part + pdst[1][0], (__float_as_uint(c[0][0] + c[1][0]) & ~1u) | tag, (__float_as_uint(c[0][1] + c[1][1]) & ~1u) | tag);
            st_relaxed_v2(g_part + pdst[1][1], (__float_as_uint(c[0][2] + c[1][2]) & ~1u) | tag, (__float_as_uint(c[0][3] + c[1][3]) & ~1u) | tag);
          }
        }
      }
      if (!last) bar_arrive(BAR_P4, REC_THREADS);
      TR(6);
      TR1(16);
      {
        const uint32_t sQX = sb + SM_QX + b * 8192;
        const int nu = (role == 0) ? 2 : 1, j0 = (role == 0) ? 0 : role + 1;
        if (warp < 3 * nu) { const int u = warp / 3, mt = warp - u * 3; rec_scores(mt, sG + 2048, sKX, sQX + (j0 + u) * 2048, sb + SM_S + u * (8 * 56 * 4), lane); }
        bar_sync(BAR_CMP, 256);
        TR1(17);
        if (warp < 4) {
          bulk_issue(s + 1);
          TR(13);
          wgmma_wait<0>();
          reg_fence(d);
          if (!last) bulk_convert(s + 1);
          TR(14);
          bar_sync(BAR_XP, 256);
          TR(15);
          const uint32_t orow = (uint32_t)(s * 32 + 8 * j0 + g) * B_HD + h * 128 + warp * 32 + 2 * t;
#pragma unroll
          for (int m = 0; m < 2; m++) {
            uint2 vx[4];
#pragma unroll
            for (int j = 0; j < 4; j++) vx[j] = lds64(sVX + (2 * warp + m) * 1024 + j * 256 + lane * 8);
            const uint2 vm = lds64(sG + 2 * 2048 + (2 * warp + m) * 256 + lane * 8);
#pragma unroll
            for (int u = 0; u < 2; u++) {
              if (u < nu) {
                uint32_t pb[5];
#pragma unroll
                for (int i = 0; i < 5; i++) asm volatile("ld.shared.u32 %0, [%1];" : "=r"(pb[i]) : "r"(sb + SM_P + u * 768 + i * 128 + lane * 4) : "memory");
                const float2 iv = lds64f(sb + SM_P + u * 768 + 640 + t * 8);
                uint32_t o0, o1;
                rec_pv(o0, o1, vm, vx, pb, iv.x, iv.y);
                *(uint32_t*)(g_oB + orow + u * 8 * B_HD + m * 16) = o0;
                *(uint32_t*)(g_oB + orow + u * 8 * B_HD + m * 16 + 8) = o1;
              }
            }
          }
          TR(22);
        } else {
          if (warp - 4 < nu) {
            const int u = warp - 4;
            uint32_t pb[1][5]; float inv[1];
            const uint32_t sa[1] = {sb + SM_S + u * (8 * 56 * 4)};
            const int lim[1] = {8 + 8 * (j0 + u) + g};
            rec_softmax<1>(pb, inv, sa, lim, lane);
#pragma unroll
            for (int i = 0; i < 5; i++) asm volatile("st.shared.u32 [%0], %1;" :: "r"(sb + SM_P + u * 768 + i * 128 + lane * 4), "r"(pb[0][i]) : "memory");
            if (t == 0) sts32f(sb + SM_P + u * 768 + 640 + g * 4, inv[0]);
          }
          TR1(18);
          bar_arrive(BAR_XP, 256);
          bulk_issue(s + 1);
          TR1(19);
          wgmma_wait<0>();
          reg_fence(d);
          TR1(20);
          if (!last) bulk_convert(s + 1);
          TR1(21);
        }
        bar_sync(BAR_CMP, 256);
        if (!last) bulk_send(s + 1);
        TR(7);
      }
      TR(8);
    }
  }
  asm volatile("barrier.cluster.arrive.release.aligned;\nbarrier.cluster.wait.acquire.aligned;" ::: "memory");
}

#define HOST_SETUP_EXTRA cudaFuncSetAttribute(rec_kernel, cudaFuncAttributeMaxDynamicSharedMemorySize, REC_SMEM);

typedef CUresult (*PFN_encodeTiled)(CUtensorMap*, CUtensorMapDataType, cuuint32_t, void*, const cuuint64_t*, const cuuint64_t*,
                                    const cuuint32_t*, const cuuint32_t*, CUtensorMapInterleave, CUtensorMapSwizzle,
                                    CUtensorMapL2promotion, CUtensorMapFloatOOBfill);
static PFN_encodeTiled g_encode = nullptr;

static CUtensorMap make_map(const void* base, int rank, const uint64_t* dims, const uint64_t* strides_bytes, const uint32_t* box, CUtensorMapSwizzle swz) {
  CUtensorMap m;
  cuuint64_t d[5], s[5]; cuuint32_t b[5], e[5];
  for (int i = 0; i < rank; i++) { d[i] = dims[i]; b[i] = box[i]; e[i] = 1; }
  for (int i = 0; i + 1 < rank; i++) s[i] = strides_bytes[i];
  CUresult r = g_encode(&m, CU_TENSOR_MAP_DATA_TYPE_BFLOAT16, rank, const_cast<void*>(base), d, s, b, e, CU_TENSOR_MAP_INTERLEAVE_NONE, swz,
                        CU_TENSOR_MAP_L2_PROMOTION_L2_256B, CU_TENSOR_MAP_FLOAT_OOB_FILL_NONE);
  if (r != CUDA_SUCCESS) fprintf(stderr, "cuTensorMapEncodeTiled failed: %d\n", (int)r);
  return m;
}
static CUtensorMap map2d(const void* base, uint64_t inner, uint64_t outer, uint64_t pitch_bytes, uint32_t box_inner, uint32_t box_outer, CUtensorMapSwizzle swz) {
  uint64_t dims[2] = {inner, outer}, st[1] = {pitch_bytes}; uint32_t box[2] = {box_inner, box_outer};
  return make_map(base, 2, dims, st, box, swz);
}
template <typename T> static void* sym_addr(const T& sym) { void* p = nullptr; cudaGetSymbolAddress(&p, sym); return p; }

struct HostState {
  bool init;
  const void* in_ptr[10];
  CUtensorMap a_x, a_wqkv, a_k, a_v, a_att, a_wo, b_o, b_wo, r_wq, r_wk, r_wv, r_wo, r_x;
  cudaStream_t s2;
  cudaEvent_t ev_fork, ev_join;
};
static HostState g_hs;

constexpr int QKV_STAGES = 6, OUTA_STAGES = 6, OUTB_STAGES = 6;
constexpr int QKV_SMEM = QKV_STAGES * GEMM_STAGE + 1024;
constexpr int OUTA_SMEM = OUTA_STAGES * GEMM_STAGE + 1024;
constexpr int OUTB_SMEM = OUTB_STAGES * GEMM_STAGE + 1024;

static void host_setup(void* const* d_in) {
  HostState& H = g_hs;
  if (!g_encode) {
    void* fn = nullptr; cudaDriverEntryPointQueryResult qr;
    cudaGetDriverEntryPoint("cuTensorMapEncodeTiled", &fn, cudaEnableDefault, &qr);
    g_encode = (PFN_encodeTiled)fn;
  }
  bool same = H.init;
  for (int i = 0; i < 9; i++) same = same && (H.in_ptr[i] == d_in[i]);
  if (same) return;
  for (int i = 0; i < 9; i++) H.in_ptr[i] = d_in[i];
  const CUtensorMapSwizzle S128 = CU_TENSOR_MAP_SWIZZLE_128B, S64 = CU_TENSOR_MAP_SWIZZLE_64B;
  H.a_x = map2d(d_in[0], DM, S_LEN, DM * 2, 64, 128, S128);
  H.a_wqkv = map2d(d_in[1], 3 * DM, DM, 3 * DM * 2, 32, 64, S64);
  H.a_k = map2d(sym_addr(g_Kp), 32, A_H * S_LEN, 64, 32, 128, S64);
  H.a_v = map2d(sym_addr(g_Vt), S_LEN, A_H * 24, S_LEN * 2, 64, 24, S128);
  H.a_att = map2d(sym_addr(g_aA), DM, S_LEN, DM * 2, 64, 128, S128);
  H.a_wo = map2d(d_in[2], DM, DM, DM * 2, 32, 64, S64);
  H.b_o = map2d(sym_addr(g_oB), B_HD, S_LEN, B_HD * 2, 64, 128, S128);
  H.b_wo = map2d(d_in[8], DM, B_HD, DM * 2, 32, 64, S64);
  H.r_wq = map2d(d_in[5], B_HD, DM, B_HD * 2, 64, 64, S128);
  H.r_wk = map2d(d_in[6], B_HD, DM, B_HD * 2, 64, 64, S128);
  H.r_wv = map2d(d_in[7], B_HD, DM, B_HD * 2, 64, 64, S128);
  H.r_wo = map2d(d_in[8], DM, B_HD, DM * 2, 32, 128, S64);
  {
    uint64_t dims[3] = {64, (uint64_t)S_LEN, 10}, st[2] = {DM * 2, 128}; uint32_t box[3] = {64, 32, 10};
    H.r_x = make_map(d_in[3], 3, dims, st, box, S128);
  }
  if (!H.init) {
    cudaFuncSetAttribute(gemm_kernel<EPI_QKV, QKV_STAGES, 1>, cudaFuncAttributeMaxDynamicSharedMemorySize, QKV_SMEM);
    cudaFuncSetAttribute(gemm_kernel<EPI_OUT, OUTA_STAGES, 1>, cudaFuncAttributeMaxDynamicSharedMemorySize, OUTA_SMEM);
    cudaFuncSetAttribute(gemm_kernel<EPI_OUT, OUTB_STAGES, 1>, cudaFuncAttributeMaxDynamicSharedMemorySize, OUTB_SMEM);
    cudaFuncSetAttribute(attnA_kernel, cudaFuncAttributeMaxDynamicSharedMemorySize, ATT_SMEM);
    HOST_SETUP_EXTRA
  }
  H.init = true;
}

static void launch_A(cudaStream_t st, bf16* out) {
  HostState& H = g_hs;
  gemm_kernel<EPI_QKV, QKV_STAGES, 1><<<dim3(12, 16), GEMM_THREADS, QKV_SMEM, st>>>(H.a_x, H.a_wqkv, DM, nullptr, 0);
  attnA_kernel<<<256, 256, ATT_SMEM, st>>>(H.a_k, H.a_v);
  gemm_kernel<EPI_OUT, OUTA_STAGES, 1><<<dim3(4, 16), GEMM_THREADS, OUTA_SMEM, st>>>(H.a_att, H.a_wo, DM, out, 0);
}
static void launch_Bout(cudaStream_t st, bf16* out) {
  HostState& H = g_hs;
  gemm_kernel<EPI_OUT, OUTB_STAGES, 1><<<dim3(4, 16), GEMM_THREADS, OUTB_SMEM, st>>>(H.b_o, H.b_wo, B_HD, out, DM);
}

static void launch_rec(cudaStream_t st, const bf16* mem0) {
  HostState& H = g_hs;
  rec_kernel<<<REC_CTAS, REC_THREADS, REC_SMEM, st>>>(H.r_wq, H.r_wk, H.r_wv, H.r_wo, H.r_x, mem0);
}

extern "C" void kernel_launch(void* const* d_in, const int* in_sizes, int n_in, void* d_out, int out_size) {
  (void)in_sizes; (void)n_in; (void)out_size;
  host_setup(d_in);
  HostState& H = g_hs;
  cudaStream_t st = cudaStreamPerThread;
  if (!H.s2) {
    cudaStreamCreateWithFlags(&H.s2, cudaStreamNonBlocking);
    cudaEventCreateWithFlags(&H.ev_fork, cudaEventDisableTiming);
    cudaEventCreateWithFlags(&H.ev_join, cudaEventDisableTiming);
  }
  cudaEventRecord(H.ev_fork, st);
  cudaStreamWaitEvent(H.s2, H.ev_fork, 0);
  launch_rec(st, (const bf16*)d_in[4]);
  launch_A(H.s2, (bf16*)d_out);
  launch_Bout(st, (bf16*)d_out);
  cudaEventRecord(H.ev_join, H.s2);
  cudaStreamWaitEvent(st, H.ev_join, 0);
}
```

```cpp
#define HAVE_REC 1

#include <cuda_runtime.h>
#include <cuda_bf16.h>
#include <cuda.h>
#include <stdint.h>
#include <stdio.h>

constexpr int S_LEN = 2048;
constexpr int DM = 640;
constexpr int OUT_LD = 1280;
constexpr int A_H = 32, A_DH = 20;
constexpr int B_H = 32, B_DH = 128, B_M = 8, B_SEG = 32, B_NSEG = 64;
constexpr int B_HD = B_H * B_DH;

typedef __nv_bfloat16 bf16;

__device__ __forceinline__ uint32_t smem_u32(const void* p) { return (uint32_t)__cvta_generic_to_shared(p); }
__device__ __forceinline__ uint32_t pack_bf16(float lo, float hi) {
  uint32_t r; asm("cvt.rn.bf16x2.f32 %0, %1, %2;" : "=r"(r) : "f"(hi), "f"(lo)); return r;
}
__device__ __forceinline__ float bf16lo(uint32_t v) { return __uint_as_float(v << 16); }
__device__ __forceinline__ float bf16hi(uint32_t v) { return __uint_as_float(v & 0xFFFF0000u); }
__device__ __forceinline__ float ex2f(float x) { float r; asm("ex2.approx.ftz.f32 %0, %1;" : "=f"(r) : "f"(x)); return r; }

__device__ __forceinline__ void mbar_init(uint32_t bar, uint32_t cnt) { asm volatile("mbarrier.init.shared::cta.b64 [%0], %1;" :: "r"(bar), "r"(cnt) : "memory"); }
__device__ __forceinline__ void mbar_expect_tx(uint32_t bar, uint32_t bytes) { asm volatile("mbarrier.arrive.expect_tx.shared::cta.b64 _, [%0], %1;" :: "r"(bar), "r"(bytes) : "memory"); }
__device__ __forceinline__ void mbar_arrive(uint32_t bar) { asm volatile("mbarrier.arrive.shared::cta.b64 _, [%0];" :: "r"(bar) : "memory"); }
__device__ __forceinline__ void mbar_arrive_cluster(uint32_t bar_cluster_addr) { asm volatile("mbarrier.arrive.shared::cluster.b64 _, [%0];" :: "r"(bar_cluster_addr) : "memory"); }
__device__ __forceinline__ bool mbar_try(uint32_t bar, uint32_t parity) {
  uint32_t ok;
  asm volatile("{\n.reg .pred p;\nmbarrier.try_wait.parity.shared::cta.b64 p, [%1], %2;\nselp.u32 %0, 1, 0, p;\n}" : "=r"(ok) : "r"(bar), "r"(parity) : "memory");
  return ok;
}
__device__ __forceinline__ bool mbar_try_cluster(uint32_t bar, uint32_t parity) {
  uint32_t ok;
  asm volatile("{\n.reg .pred p;\nmbarrier.try_wait.parity.acquire.cluster.shared::cta.b64 p, [%1], %2;\nselp.u32 %0, 1, 0, p;\n}" : "=r"(ok) : "r"(bar), "r"(parity) : "memory");
  return ok;
}
constexpr uint32_t SPIN_LIMIT = 1u << 20;
__device__ unsigned g_timeout_flag;
__device__ __forceinline__ void mbar_wait(uint32_t bar, uint32_t parity) {
  uint32_t n = 0;
  while (!mbar_try(bar, parity)) { if (++n > SPIN_LIMIT) { g_timeout_flag = 1; break; } }
}
__device__ __forceinline__ void mbar_wait_cluster(uint32_t bar, uint32_t parity) {
  uint32_t n = 0;
  while (!mbar_try_cluster(bar, parity)) { if (++n > SPIN_LIMIT) { g_timeout_flag = 2; break; } }
}
__device__ __forceinline__ void fence_mbar_init() { asm volatile("fence.mbarrier_init.release.cluster;" ::: "memory"); }
__device__ __forceinline__ void fence_proxy_async() { asm volatile("fence.proxy.async.shared::cta;" ::: "memory"); }
__device__ __forceinline__ void bar_sync(int id, int n) { __syncwarp(); asm volatile("bar.sync %0, %1;" :: "r"(id), "r"(n) : "memory"); }
__device__ __forceinline__ void bar_arrive(int id, int n) { __syncwarp(); asm volatile("bar.arrive %0, %1;" :: "r"(id), "r"(n) : "memory"); }

__device__ __forceinline__ void tma_load_2d(uint32_t dst, const CUtensorMap* tm, int c0, int c1, uint32_t bar) {
  asm volatile("cp.async.bulk.tensor.2d.shared::cta.global.mbarrier::complete_tx::bytes [%0], [%1, {%3, %4}], [%2];"
               :: "r"(dst), "l"(tm), "r"(bar), "r"(c0), "r"(c1) : "memory");
}
__device__ __forceinline__ void tma_load_3d(uint32_t dst, const CUtensorMap* tm, int c0, int c1, int c2, uint32_t bar) {
  asm volatile("cp.async.bulk.tensor.3d.shared::cta.global.mbarrier::complete_tx::bytes [%0], [%1, {%3, %4, %5}], [%2];"
               :: "r"(dst), "l"(tm), "r"(bar), "r"(c0), "r"(c1), "r"(c2) : "memory");
}
__device__ __forceinline__ void tma_load_3d_mc(uint32_t dst, const CUtensorMap* tm, int c0, int c1, int c2, uint32_t bar, uint16_t mask) {
  asm volatile("cp.async.bulk.tensor.3d.shared::cluster.global.mbarrier::complete_tx::bytes.multicast::cluster [%0], [%1, {%3, %4, %5}], [%2], %6;"
               :: "r"(dst), "l"(tm), "r"(bar), "r"(c0), "r"(c1), "r"(c2), "h"(mask) : "memory");
}
__device__ __forceinline__ void tma_prefetch_desc(const CUtensorMap* tm) { asm volatile("prefetch.tensormap [%0];" :: "l"(tm) : "memory"); }

__device__ __forceinline__ void wgmma_fence() { asm volatile("wgmma.fence.sync.aligned;" ::: "memory"); }
__device__ __forceinline__ void wgmma_commit() { asm volatile("wgmma.commit_group.sync.aligned;" ::: "memory"); }
template <int N> __device__ __forceinline__ void wgmma_wait() { asm volatile("wgmma.wait_group.sync.aligned %0;" :: "n"(N) : "memory"); }
__device__ __forceinline__ uint64_t make_desc(uint32_t addr, uint32_t lbo_bytes, uint32_t sbo_bytes, uint32_t swz) {
  return (uint64_t)((addr & 0x3FFFF) >> 4) | ((uint64_t)((lbo_bytes & 0x3FFFF) >> 4) << 16) |
         ((uint64_t)((sbo_bytes & 0x3FFFF) >> 4) << 32) | ((uint64_t)swz << 62);
}
template <int NREG> __device__ __forceinline__ void reg_fence(float (&d)[NREG]) {
#pragma unroll
  for (int i = 0; i < NREG; i++) asm volatile("" : "+f"(d[i]) :: "memory");
}
__device__ __forceinline__ void mma16816(float (&c)[4], const uint32_t (&a)[4], uint32_t b0, uint32_t b1) {
  asm volatile("mma.sync.aligned.m16n8k16.row.col.f32.bf16.bf16.f32 {%0,%1,%2,%3}, {%4,%5,%6,%7}, {%8,%9}, {%0,%1,%2,%3};"
               : "+f"(c[0]), "+f"(c[1]), "+f"(c[2]), "+f"(c[3])
               : "r"(a[0]), "r"(a[1]), "r"(a[2]), "r"(a[3]), "r"(b0), "r"(b1));
}
__device__ __forceinline__ uint32_t movmatrix_t(uint32_t v) {
  uint32_t r; asm volatile("movmatrix.sync.aligned.m8n8.trans.b16 %0, %1;" : "=r"(r) : "r"(v)); return r;
}
__device__ __forceinline__ void ldsm_x4(uint32_t (&r)[4], uint32_t addr) {
  asm volatile("ldmatrix.sync.aligned.m8n8.x4.shared.b16 {%0,%1,%2,%3}, [%4];" : "=r"(r[0]), "=r"(r[1]), "=r"(r[2]), "=r"(r[3]) : "r"(addr) : "memory");
}
__device__ __forceinline__ void ldsm_x4_t(uint32_t (&r)[4], uint32_t addr) {
  asm volatile("ldmatrix.sync.aligned.m8n8.x4.trans.shared.b16 {%0,%1,%2,%3}, [%4];" : "=r"(r[0]), "=r"(r[1]), "=r"(r[2]), "=r"(r[3]) : "r"(addr) : "memory");
}

#define TL_START(k)
#define TL_END(k)

__device__ __forceinline__ void wgmma_rs_n32(float (&d)[16], const uint32_t (&a)[4], uint64_t db, int scale_d) {
  asm volatile("{\n.reg .pred p;\nsetp.ne.b32 p, %21, 0;\n"
    "wgmma.mma_async.sync.aligned.m64n32k16.f32.bf16.bf16 "
    "{%0, %1, %2, %3, %4, %5, %6, %7, %8, %9, %10, %11, %12, %13, %14, %15}, "
    "{%16, %17, %18, %19}, %20, p, 1, 1, 0;\n}\n"
    : "+f"(d[0]), "+f"(d[1]), "+f"(d[2]), "+f"(d[3]), "+f"(d[4]), "+f"(d[5]), "+f"(d[6]), "+f"(d[7]), "+f"(d[8]), "+f"(d[9]), "+f"(d[10]), "+f"(d[11]), "+f"(d[12]), "+f"(d[13]), "+f"(d[14]), "+f"(d[15])
    : "r"(a[0]), "r"(a[1]), "r"(a[2]), "r"(a[3]), "l"(db), "r"(scale_d));
}
__device__ __forceinline__ void wgmma_ss_n160_tb(float (&d)[80], uint64_t da, uint64_t db, int scale_d) {
  asm volatile("{\n.reg .pred p;\nsetp.ne.b32 p, %82, 0;\n"
    "wgmma.mma_async.sync.aligned.m64n160k16.f32.bf16.bf16 "
    "{%0, %1, %2, %3, %4, %5, %6, %7, %8, %9, %10, %11, %12, %13, %14, %15, %16, %17, %18, %19, %20, %21, %22, %23, %24, %25, %26, %27, %28, %29, %30, %31, %32, %33, %34, %35, %36, %37, %38, %39, %40, %41, %42, %43, %44, %45, %46, %47, %48, %49, %50, %51, %52, %53, %54, %55, %56, %57, %58, %59, %60, %61, %62, %63, %64, %65, %66, %67, %68, %69, %70, %71, %72, %73, %74, %75, %76, %77, %78, %79}, "
    "%80, %81, p, 1, 1, 0, 1;\n}\n"
    : "+f"(d[0]), "+f"(d[1]), "+f"(d[2]), "+f"(d[3]), "+f"(d[4]), "+f"(d[5]), "+f"(d[6]), "+f"(d[7]), "+f"(d[8]), "+f"(d[9]), "+f"(d[10]), "+f"(d[11]), "+f"(d[12]), "+f"(d[13]), "+f"(d[14]), "+f"(d[15]), "+f"(d[16]), "+f"(d[17]), "+f"(d[18]), "+f"(d[19]), "+f"(d[20]), "+f"(d[21]), "+f"(d[22]), "+f"(d[23]), "+f"(d[24]), "+f"(d[25]), "+f"(d[26]), "+f"(d[27]), "+f"(d[28]), "+f"(d[29]), "+f"(d[30]), "+f"(d[31]), "+f"(d[32]), "+f"(d[33]), "+f"(d[34]), "+f"(d[35]), "+f"(d[36]), "+f"(d[37]), "+f"(d[38]), "+f"(d[39]), "+f"(d[40]), "+f"(d[41]), "+f"(d[42]), "+f"(d[43]), "+f"(d[44]), "+f"(d[45]), "+f"(d[46]), "+f"(d[47]), "+f"(d[48]), "+f"(d[49]), "+f"(d[50]), "+f"(d[51]), "+f"(d[52]), "+f"(d[53]), "+f"(d[54]), "+f"(d[55]), "+f"(d[56]), "+f"(d[57]), "+f"(d[58]), "+f"(d[59]), "+f"(d[60]), "+f"(d[61]), "+f"(d[62]), "+f"(d[63]), "+f"(d[64]), "+f"(d[65]), "+f"(d[66]), "+f"(d[67]), "+f"(d[68]), "+f"(d[69]), "+f"(d[70]), "+f"(d[71]), "+f"(d[72]), "+f"(d[73]), "+f"(d[74]), "+f"(d[75]), "+f"(d[76]), "+f"(d[77]), "+f"(d[78]), "+f"(d[79])
    : "l"(da), "l"(db), "r"(scale_d));
}

__device__ bf16 g_Qp[A_H * S_LEN * 32];
__device__ bf16 g_Kp[A_H * S_LEN * 32];
__device__ bf16 g_Vt[A_H * 24 * S_LEN];
__device__ float g_kmax2[16 * A_H];
__device__ bf16 g_aA[S_LEN * DM];
__device__ bf16 g_oB[S_LEN * B_HD];
__device__ unsigned g_att_ctr;

constexpr int GEMM_THREADS = 288;
constexpr int GEMM_BN = 160;
constexpr int GEMM_A_BYTES = 128 * 128;
constexpr int GEMM_B_BYTES = 5 * 4096;
constexpr int GEMM_STAGE = GEMM_A_BYTES + GEMM_B_BYTES;
enum { EPI_QKV = 0, EPI_OUT = 1, EPI_OUT_SK = 2 };
constexpr int EPI_PITCH = 336;

__device__ __forceinline__ void cluster_sync() { asm volatile("barrier.cluster.arrive.release.aligned;\nbarrier.cluster.wait.acquire.aligned;" ::: "memory"); }
__device__ __forceinline__ uint32_t mapa_u32(uint32_t addr, uint32_t rank) { uint32_t r; asm("mapa.shared::cluster.u32 %0, %1, %2;" : "=r"(r) : "r"(addr), "r"(rank)); return r; }

template <int EPI, int STAGES, int MINB>
__global__ void __launch_bounds__(GEMM_THREADS, MINB)
gemm_kernel(const __grid_constant__ CUtensorMap tmA, const __grid_constant__ CUtensorMap tmB, int K, bf16* __restrict__ out, int out_col0) {
  extern __shared__ uint8_t smem_raw[];
  const uint32_t sbase = (smem_u32(smem_raw) + 1023) & ~1023u;
  uint8_t* sgen = smem_raw + (sbase - smem_u32(smem_raw));
  __shared__ __align__(8) uint64_t s_full[STAGES], s_empty[STAGES];
  __shared__ unsigned s_kmax[8];
  const int tid = threadIdx.x, warp = tid >> 5, lane = tid & 31;
  const int n_tile = blockIdx.x, m_tile = blockIdx.y;
  constexpr int TLK = (EPI == EPI_QKV) ? 1 : (EPI == EPI_OUT ? 3 : 4); (void)TLK;
  TL_START(TLK);
  const int nk = (EPI == EPI_OUT_SK) ? K / 128 : K / 64;
  const int k0 = (EPI == EPI_OUT_SK) ? (int)blockIdx.z * nk : 0;
  if (tid == 0) {
    for (int i = 0; i < STAGES; i++) { mbar_init(smem_u32(&s_full[i]), 1); mbar_init(smem_u32(&s_empty[i]), 2); }
    fence_mbar_init();
  }
  if (tid < 8) s_kmax[tid] = 0;
  if (EPI == EPI_QKV && tid == 0 && n_tile == 0 && m_tile == 0) g_att_ctr = 0;
  __syncthreads();
  if (warp == 8) {
    if (lane == 0) {
      for (int k = 0; k < nk; k++) {
        const int st = k % STAGES;
        if (k >= STAGES) mbar_wait(smem_u32(&s_empty[st]), ((k / STAGES) - 1) & 1);
        const uint32_t fb = smem_u32(&s_full[st]), sa = sbase + st * GEMM_STAGE;
        mbar_expect_tx(fb, GEMM_STAGE);
        tma_load_2d(sa, &tmA, (k0 + k) * 64, m_tile * 128, fb);
#pragma unroll
        for (int b = 0; b < 5; b++) tma_load_2d(sa + GEMM_A_BYTES + b * 4096, &tmB, n_tile * GEMM_BN + b * 32, (k0 + k) * 64, fb);
      }
    }
    if (EPI == EPI_OUT_SK) { __syncwarp(); cluster_sync(); cluster_sync(); cluster_sync(); }
    return;
  }
  const int wg = warp >> 2;
  float acc[80];
  const uint64_t dA0 = make_desc(sbase + wg * 8192, 16, 1024, 1), dB0 = make_desc(sbase + GEMM_A_BYTES, 4096, 512, 2);
  for (int k = 0; k < nk; k++) {
    const int st = k % STAGES;
    mbar_wait(smem_u32(&s_full[st]), (k / STAGES) & 1);
    const uint64_t dA = dA0 + st * (GEMM_STAGE >> 4), dB = dB0 + st * (GEMM_STAGE >> 4);
    wgmma_fence();
#pragma unroll
    for (int kk = 0; kk < 4; kk++) wgmma_ss_n160_tb(acc, dA + kk * 2, dB + kk * 64, (k > 0 || kk > 0) ? 1 : 0);
    wgmma_commit();
    if (k > 0) {
      wgmma_wait<1>();
      if ((tid & 127) == 0) mbar_arrive(smem_u32(&s_empty[(k - 1) % STAGES]));
    }
  }
  wgmma_wait<0>();
  reg_fence(acc);
  bar_sync(1, 256);

  const int g = lane >> 2, t = lane & 3;
  const int lrow = wg * 64 + (warp & 3) * 16 + g;
  if (EPI == EPI_OUT_SK) {
    const uint32_t rank = blockIdx.z;
    cluster_sync();
    const uint32_t remote = mapa_u32(sbase + tid * 16, rank ^ 1);
#pragma unroll
    for (int i = 0; i < 10; i++) {
      const float* a = rank ? &acc[4 * i] : &acc[40 + 4 * i];
      asm volatile("st.shared::cluster.v4.f32 [%0], {%1,%2,%3,%4};" :: "r"(remote + i * 4096), "f"(rank ? acc[4 * i] : acc[40 + 4 * i]), "f"(rank ? acc[4 * i + 1] : acc[41 + 4 * i]),
                   "f"(rank ? acc[4 * i + 2] : acc[42 + 4 * i]), "f"(rank ? acc[4 * i + 3] : acc[43 + 4 * i]) : "memory");
      (void)a;
    }
    cluster_sync();
    uint32_t pk[10][2];
#pragma unroll
    for (int i = 0; i < 10; i++) {
      const float4 r = *(const float4*)(sgen + i * 4096 + tid * 16);
      const float a0 = rank ? acc[40 + 4 * i] : acc[4 * i], a1 = rank ? acc[41 + 4 * i] : acc[4 * i + 1];
      const float a2 = rank ? acc[42 + 4 * i] : acc[4 * i + 2], a3 = rank ? acc[43 + 4 * i] : acc[4 * i + 3];
      pk[i][0] = pack_bf16(a0 + r.x, a1 + r.y); pk[i][1] = pack_bf16(a2 + r.z, a3 + r.w);
    }
    bar_sync(1, 256);
    constexpr int HP = 176;
#pragma unroll
    for (int i = 0; i < 10; i++) {
      *(uint32_t*)(sgen + lrow * HP + (8 * i + 2 * t) * 2) = pk[i][0];
      *(uint32_t*)(sgen + (lrow + 8) * HP + (8 * i + 2 * t) * 2) = pk[i][1];
    }
    bar_sync(1, 256);
    for (int i = tid; i < 128 * 10; i += 256) {
      const int r = i / 10, c = i - r * 10;
      *(uint4*)(out + (size_t)(m_tile * 128 + r) * OUT_LD + out_col0 + n_tile * GEMM_BN + rank * 80 + c * 8) = *(const uint4*)(sgen + r * HP + c * 16);
    }
    cluster_sync();
    TL_END(TLK);
    return;
  }
  const int sec = (EPI == EPI_QKV) ? (n_tile >> 2) : 0;
  if (EPI == EPI_OUT || sec < 2) {
#pragma unroll
    for (int j = 0; j < 20; j++) {
      *(uint32_t*)(sgen + lrow * EPI_PITCH + (8 * j + 2 * t) * 2) = pack_bf16(acc[4 * j], acc[4 * j + 1]);
      *(uint32_t*)(sgen + (lrow + 8) * EPI_PITCH + (8 * j + 2 * t) * 2) = pack_bf16(acc[4 * j + 2], acc[4 * j + 3]);
    }
    bar_sync(1, 256);
    if (EPI == EPI_OUT) {
      for (int i = tid; i < 128 * 20; i += 256) {
        const int r = i / 20, c = i - r * 20;
        const uint4 v = *(const uint4*)(sgen + r * EPI_PITCH + c * 16);
        *(uint4*)(out + (size_t)(m_tile * 128 + r) * OUT_LD + out_col0 + n_tile * GEMM_BN + c * 8) = v;
      }
    } else {
      const int h0 = (n_tile & 3) * 8, pc = tid & 3;
      bf16* dst = (sec == 0 ? g_Qp : g_Kp);
      const uint32_t aug = (sec == 1) ? 0x3F803F80u : 0u;
#pragma unroll 1
      for (int hh = 0; hh < 8; hh++) {
        float mx = 0.f;
#pragma unroll
        for (int hf = 0; hf < 2; hf++) {
          const int r = hf * 64 + (tid >> 2);
          const uint8_t* src = sgen + r * EPI_PITCH + hh * 40 + pc * 16;
          uint4 v = make_uint4(0u, 0u, 0u, 0u);
          if (pc < 3) { const uint2 a = *(const uint2*)src; v.x = a.x; v.y = a.y; }
          if (pc < 2) { const uint2 b = *(const uint2*)(src + 8); v.z = b.x; v.w = b.y; }
          if (sec == 1) {
            float ss = bf16lo(v.x) * bf16lo(v.x) + bf16hi(v.x) * bf16hi(v.x) + bf16lo(v.y) * bf16lo(v.y) + bf16hi(v.y) * bf16hi(v.y)
                     + bf16lo(v.z) * bf16lo(v.z) + bf16hi(v.z) * bf16hi(v.z) + bf16lo(v.w) * bf16lo(v.w) + bf16hi(v.w) * bf16hi(v.w);
            ss += __shfl_xor_sync(~0u, ss, 1); ss += __shfl_xor_sync(~0u, ss, 2);
            if (!(ss == ss)) ss = __uint_as_float(0x7F800000u);
            mx = fmaxf(mx, ss);
          }
          if (pc == 2) v.z = aug;
          *(uint4*)(dst + ((size_t)(h0 + hh) * S_LEN + m_tile * 128 + r) * 32 + pc * 8) = v;
        }
        if (sec == 1) {
          mx = fmaxf(mx, __shfl_xor_sync(~0u, mx, 4)); mx = fmaxf(mx, __shfl_xor_sync(~0u, mx, 8)); mx = fmaxf(mx, __shfl_xor_sync(~0u, mx, 16));
          if (lane == 0) atomicMax(&s_kmax[hh], __float_as_uint(mx));
        }
      }
      if (sec == 1) {
        bar_sync(1, 256);
        if (tid < 8) g_kmax2[m_tile * A_H + h0 + tid] = __uint_as_float(s_kmax[tid]);
      }
    }
  } else {
    constexpr int VP = 272;
    const int ltok = wg * 64 + (warp & 3) * 16 + 2 * t;
#pragma unroll
    for (int j = 0; j < 20; j++) {
      *(uint32_t*)(sgen + (8 * j + g) * VP + ltok * 2) = movmatrix_t(pack_bf16(acc[4 * j], acc[4 * j + 1]));
      *(uint32_t*)(sgen + (8 * j + g) * VP + (ltok + 8) * 2) = movmatrix_t(pack_bf16(acc[4 * j + 2], acc[4 * j + 3]));
    }
    bar_sync(1, 256);
    const int h0 = (n_tile & 3) * 8;
    for (int i = tid; i < 8 * 24 * 16; i += 256) {
      const int ch = i & 15, rr = i >> 4, hh = rr / 24, d = rr - hh * 24;
      uint4 v;
      if (d < 20) v = *(const uint4*)(sgen + (hh * 20 + d) * VP + ch * 16);
      else { const uint32_t val = (d == 20) ? 0x3F803F80u : 0u; v = make_uint4(val, val, val, val); }
      *(uint4*)(g_Vt + ((size_t)(h0 + hh) * 24 + d) * S_LEN + m_tile * 128 + ch * 8) = v;
    }
  }
  TL_END(TLK);
}

constexpr int ATT_STAGES = 3;
constexpr int ATT_STAGE_BYTES = 8192 + 6144;
constexpr int ATT_SMEM = ATT_STAGES * ATT_STAGE_BYTES + 1024;
constexpr int ATT_ITEMS = A_H * (S_LEN / 128);
constexpr float A_SCALE_LOG2E = 0.22360679774997896f * 1.4426950408889634f;

__device__ __forceinline__ uint32_t bf16_up_bits(float x) {
  uint32_t u = __float_as_uint(x);
  if ((u & 0x7F800000u) == 0x7F800000u) return u >> 16;
  uint32_t r = (u & 0x80000000u) ? u : u + 0xFFFFu;
  return r >> 16;
}
__device__ __forceinline__ void mma16816_z(float (&d)[4], const uint32_t (&a)[4], uint32_t b0, uint32_t b1) {
  asm("mma.sync.aligned.m16n8k16.row.col.f32.bf16.bf16.f32 {%0,%1,%2,%3}, {%4,%5,%6,%7}, {%8,%9}, {%10,%10,%10,%10};"
      : "=f"(d[0]), "=f"(d[1]), "=f"(d[2]), "=f"(d[3])
      : "r"(a[0]), "r"(a[1]), "r"(a[2]), "r"(a[3]), "r"(b0), "r"(b1), "f"(0.f));
}
__device__ __forceinline__ void mma16816_nv(float (&c)[4], const uint32_t (&a)[4], uint32_t b0, uint32_t b1) {
  asm("mma.sync.aligned.m16n8k16.row.col.f32.bf16.bf16.f32 {%0,%1,%2,%3}, {%4,%5,%6,%7}, {%8,%9}, {%0,%1,%2,%3};"
      : "+f"(c[0]), "+f"(c[1]), "+f"(c[2]), "+f"(c[3])
      : "r"(a[0]), "r"(a[1]), "r"(a[2]), "r"(a[3]), "r"(b0), "r"(b1));
}
__device__ __forceinline__ void mma1688_nv(float (&c)[4], uint32_t a0, uint32_t a1, uint32_t b0) {
  asm("mma.sync.aligned.m16n8k8.row.col.f32.bf16.bf16.f32 {%0,%1,%2,%3}, {%4,%5}, {%6}, {%0,%1,%2,%3};"
      : "+f"(c[0]), "+f"(c[1]), "+f"(c[2]), "+f"(c[3]) : "r"(a0), "r"(a1), "r"(b0));
}
__device__ __forceinline__ void ldsm_x2(uint32_t& r0, uint32_t& r1, uint32_t addr) {
  asm volatile("ldmatrix.sync.aligned.m8n8.x2.shared.b16 {%0,%1}, [%2];" : "=r"(r0), "=r"(r1) : "r"(addr) : "memory");
}
__device__ __forceinline__ void attn_load_q(uint32_t (&qa)[2][2][4], int h, int row0, int t) {
#pragma unroll
  for (int m = 0; m < 2; m++) {
    const bf16* q0 = g_Qp + ((size_t)h * S_LEN + row0 + 16 * m) * 32 + 2 * t;
#pragma unroll
    for (int ks = 0; ks < 2; ks++) {
      qa[m][ks][0] = *(const uint32_t*)(q0 + 16 * ks);
      qa[m][ks][1] = *(const uint32_t*)(q0 + 16 * ks + 8 * 32);
      qa[m][ks][2] = *(const uint32_t*)(q0 + 16 * ks + 8);
      qa[m][ks][3] = *(const uint32_t*)(q0 + 16 * ks + 8 + 8 * 32);
    }
  }
}
__device__ __forceinline__ void attn_store(const float (&o)[2][3][4], const float (&l)[2][2], int h, int row0, int t) {
#pragma unroll
  for (int m = 0; m < 2; m++) {
    const float i0 = 1.0f / l[m][0], i1 = 1.0f / l[m][1];
    bf16* o0 = g_aA + (size_t)(row0 + 16 * m) * DM + h * A_DH + 2 * t;
#pragma unroll
    for (int j = 0; j < 3; j++) {
      if (j < 2 || t < 2) {
        *(uint32_t*)(o0 + 8 * j) = pack_bf16(o[m][j][0] * i0, o[m][j][1] * i0);
        *(uint32_t*)(o0 + 8 * j + 8 * DM) = pack_bf16(o[m][j][2] * i1, o[m][j][3] * i1);
      }
    }
  }
}
__device__ __noinline__ void attn_exact(int h, int row0, int lane) {
  const int g = lane >> 2, t = lane & 3;
  uint32_t qa[2][2][4];
  attn_load_q(qa, h, row0, t);
  const bf16* kp = g_Kp + ((size_t)h * S_LEN + g) * 32 + 2 * t;
  const bf16* vp = g_Vt + ((size_t)h * 24 + g) * S_LEN + 2 * t;
  float mx[2][2] = {{-INFINITY, -INFINITY}, {-INFINITY, -INFINITY}};
  float o[2][3][4];
#pragma unroll
  for (int m = 0; m < 2; m++)
#pragma unroll
    for (int d = 0; d < 3; d++) { o[m][d][0] = 0.f; o[m][d][1] = 0.f; o[m][d][2] = 0.f; o[m][d][3] = 0.f; }
#pragma unroll 1
  for (int pass = 0; pass < 2; pass++) {
#pragma unroll 1
    for (int k0 = 0; k0 < S_LEN; k0 += 16) {
      float s[2][2][4];
#pragma unroll
      for (int nt = 0; nt < 2; nt++) {
        const bf16* kr = kp + (size_t)(k0 + 8 * nt) * 32;
        const uint32_t b0 = *(const uint32_t*)kr, b1 = *(const uint32_t*)(kr + 8), b2 = *(const uint32_t*)(kr + 16), b3 = *(const uint32_t*)(kr + 24);
#pragma unroll
        for (int m = 0; m < 2; m++) { mma16816_z(s[m][nt], qa[m][0], b0, b1); mma16816_nv(s[m][nt], qa[m][1], b2, b3); }
      }
      if (pass == 0) {
#pragma unroll
        for (int m = 0; m < 2; m++)
#pragma unroll
          for (int nt = 0; nt < 2; nt++) {
            mx[m][0] = fmaxf(mx[m][0], fmaxf(s[m][nt][0], s[m][nt][1]));
            mx[m][1] = fmaxf(mx[m][1], fmaxf(s[m][nt][2], s[m][nt][3]));
          }
      } else {
        uint32_t p[2][4];
#pragma unroll
        for (int m = 0; m < 2; m++) {
          p[m][0] = pack_bf16(ex2f(s[m][0][0] * A_SCALE_LOG2E), ex2f(s[m][0][1] * A_SCALE_LOG2E));
          p[m][1] = pack_bf16(ex2f(s[m][0][2] * A_SCALE_LOG2E), ex2f(s[m][0][3] * A_SCALE_LOG2E));
          p[m][2] = pack_bf16(ex2f(s[m][1][0] * A_SCALE_LOG2E), ex2f(s[m][1][1] * A_SCALE_LOG2E));
          p[m][3] = pack_bf16(ex2f(s[m][1][2] * A_SCALE_LOG2E), ex2f(s[m][1][3] * A_SCALE_LOG2E));
        }
#pragma unroll
        for (int d = 0; d < 3; d++) {
          const bf16* vr = vp + (size_t)(8 * d) * S_LEN + k0;
          const uint32_t b0 = *(const uint32_t*)vr, b1 = *(const uint32_t*)(vr + 8);
#pragma unroll
          for (int m = 0; m < 2; m++) mma16816_nv(o[m][d], p[m], b0, b1);
        }
      }
    }
    if (pass == 0) {
#pragma unroll
      for (int m = 0; m < 2; m++)
#pragma unroll
        for (int r = 0; r < 2; r++) {
          float v = mx[m][r];
          v = fmaxf(v, __shfl_xor_sync(~0u, v, 1)); v = fmaxf(v, __shfl_xor_sync(~0u, v, 2));
          if (t == 2) {
            const uint32_t hi = pack_bf16(v, 0.f) & 0xFFFFu;
            const uint32_t lo = pack_bf16(v - bf16lo(hi), 0.f) & 0xFFFFu;
            qa[m][1][r] = (hi | (lo << 16)) ^ 0x80008000u;
          }
        }
    }
  }
  float l[2][2];
#pragma unroll
  for (int m = 0; m < 2; m++) {
    l[m][0] = __shfl_sync(~0u, o[m][2][0], (lane & ~3) | 2);
    l[m][1] = __shfl_sync(~0u, o[m][2][2], (lane & ~3) | 2);
  }
  attn_store(o, l, h, row0, t);
}

__global__ void __launch_bounds__(128, 4)
attnA_kernel(const __grid_constant__ CUtensorMap tmK, const __grid_constant__ CUtensorMap tmV) {
  extern __shared__ uint8_t smem_raw[];
  const uint32_t sbase = (smem_u32(smem_raw) + 1023) & ~1023u;
  __shared__ __align__(8) uint64_t s_full[ATT_STAGES], s_empty[ATT_STAGES];
  __shared__ unsigned s_item[3];
  const int tid = threadIdx.x, warp = tid >> 5, lane = tid & 31;
  TL_START(2);
  if (tid == 0) {
    for (int i = 0; i < ATT_STAGES; i++) { mbar_init(smem_u32(&s_full[i]), 1); mbar_init(smem_u32(&s_empty[i]), 4); }
    fence_mbar_init();
    s_item[2] = atomicAdd(&g_att_ctr, 1u);
  }
  __syncthreads();
  unsigned cur = s_item[2], round = 0;
  if (cur >= ATT_ITEMS) return;
  int it = 0;
  int base = 0;
  auto load_stage = [&](int st) {
    if (lane == 0) {
      if (st - base >= 16) mbar_wait(smem_u32(&s_empty[st % ATT_STAGES]), ((st / ATT_STAGES) - 1) & 1);
      const unsigned item = (st - base < 16) ? cur : *(volatile unsigned*)&s_item[round & 1];
      if (item < ATT_ITEMS) {
        const int h = item >> 4, j = (st - base) & 15, slot = st % ATT_STAGES;
        const uint32_t fb = smem_u32(&s_full[slot]), sa = sbase + slot * ATT_STAGE_BYTES;
        if (st >= ATT_STAGES) mbar_wait(smem_u32(&s_empty[slot]), ((st / ATT_STAGES) - 1) & 1);
        mbar_expect_tx(fb, ATT_STAGE_BYTES);
        tma_load_2d(sa, &tmK, 0, h * S_LEN + j * 128, fb);
        tma_load_2d(sa + 8192, &tmV, j * 128, h * 24, fb);
        tma_load_2d(sa + 8192 + 3072, &tmV, j * 128 + 64, h * 24, fb);
      }
    }
    __syncwarp();
  };
  if (warp < 2) load_stage(warp);

  const int g = lane >> 2, t = lane & 3;
  const uint32_t koff = (lane & 7) * 64 + (((lane >> 3) ^ ((lane & 7) >> 1)) << 4);
  const uint32_t voff01 = 8192 + ((lane & 7) + 8 * (lane >> 4)) * 128 + ((((lane >> 3) & 1) ^ (lane & 7)) << 4);
  const uint32_t voff2 = 8192 + ((lane & 7) + 16) * 128 + ((((lane >> 3) & 1) ^ (lane & 7)) << 4);
#pragma unroll 1
  while (true) {
    const int h = cur >> 4;
    const int row0 = (cur & 15) * 128 + warp * 32 + g;
    uint32_t qa[2][2][4];
    attn_load_q(qa, h, row0, t);
    {
      float km = 0.f;
#pragma unroll
      for (int i = 0; i < 16; i++) { const float v = g_kmax2[i * A_H + h]; km = (v > km || !(v == v)) ? v : km; }
#pragma unroll
      for (int m = 0; m < 2; m++) {
        float n0 = 0.f, n1 = 0.f;
#pragma unroll
        for (int ks = 0; ks < 2; ks++) {
          const uint32_t* a = qa[m][ks];
          n0 += bf16lo(a[0]) * bf16lo(a[0]) + bf16hi(a[0]) * bf16hi(a[0]) + bf16lo(a[2]) * bf16lo(a[2]) + bf16hi(a[2]) * bf16hi(a[2]);
          n1 += bf16lo(a[1]) * bf16lo(a[1]) + bf16hi(a[1]) * bf16hi(a[1]) + bf16lo(a[3]) * bf16lo(a[3]) + bf16hi(a[3]) * bf16hi(a[3]);
        }
        n0 += __shfl_xor_sync(~0u, n0, 1); n0 += __shfl_xor_sync(~0u, n0, 2);
        n1 += __shfl_xor_sync(~0u, n1, 1); n1 += __shfl_xor_sync(~0u, n1, 2);
        const float b0 = sqrtf(n0 * km) * 1.0078125f, b1 = sqrtf(n1 * km) * 1.0078125f;
        if (t == 2) {
          qa[m][1][0] = bf16_up_bits(b0) | 0x8000u;
          qa[m][1][1] = bf16_up_bits(b1) | 0x8000u;
        }
      }
    }
    float o[2][3][4];
#pragma unroll
    for (int m = 0; m < 2; m++)
#pragma unroll
      for (int d = 0; d < 3; d++) { o[m][d][0] = 0.f; o[m][d][1] = 0.f; o[m][d][2] = 0.f; o[m][d][3] = 0.f; }
    auto scores = [&](float (&s)[2][2][4], uint32_t kaddr) {
#pragma unroll
      for (int nt = 0; nt < 2; nt++) {
        uint32_t kb[4];
        ldsm_x4(kb, kaddr + nt * 512);
#pragma unroll
        for (int m = 0; m < 2; m++) {
          mma16816_z(s[m][nt], qa[m][0], kb[0], kb[1]); mma16816_nv(s[m][nt], qa[m][1], kb[2], kb[3]);
        }
      }
    };
    auto exp_pv = [&](const float (&s)[2][2][4], uint32_t sa, int blk) {
      constexpr float SC = A_SCALE_LOG2E;
      uint32_t vb[4], vc0, vc1;
      const uint32_t vo = sa + (blk >> 2) * 3072, vx = (blk & 3) * 32;
      ldsm_x4(vb, vo + (voff01 ^ vx));
      ldsm_x2(vc0, vc1, vo + (voff2 ^ vx));
      uint32_t p[2][4];
#pragma unroll
      for (int m = 0; m < 2; m++) {
        p[m][0] = pack_bf16(ex2f(s[m][0][0] * SC), ex2f(s[m][0][1] * SC));
        p[m][1] = pack_bf16(ex2f(s[m][0][2] * SC), ex2f(s[m][0][3] * SC));
        p[m][2] = pack_bf16(ex2f(s[m][1][0] * SC), ex2f(s[m][1][1] * SC));
        p[m][3] = pack_bf16(ex2f(s[m][1][2] * SC), ex2f(s[m][1][3] * SC));
      }
#pragma unroll
      for (int m = 0; m < 2; m++) {
        mma16816_nv(o[m][0], p[m], vb[0], vb[1]); mma16816_nv(o[m][1], p[m], vb[2], vb[3]); mma16816_nv(o[m][2], p[m], vc0, vc1);
      }
    };
    float sA[2][2][4], sB[2][2][4];
    mbar_wait(smem_u32(&s_full[it % ATT_STAGES]), (it / ATT_STAGES) & 1);
    scores(sA, sbase + (it % ATT_STAGES) * ATT_STAGE_BYTES + koff);
#pragma unroll 1
    for (int j = 0; j < 16; j++, it++) {
      const uint32_t sa = sbase + (it % ATT_STAGES) * ATT_STAGE_BYTES;
      if (j == 4 && tid == 0) *(volatile unsigned*)&s_item[round & 1] = atomicAdd(&g_att_ctr, 1u);
      if (warp == ((it + 2) & 3)) load_stage(it + 2);
#pragma unroll
      for (int bp = 0; bp < 4; bp++) {
        scores(sB, sa + koff + (2 * bp + 1) * 1024);
        exp_pv(sA, sa, 2 * bp);
        if (bp < 3) scores(sA, sa + koff + (2 * bp + 2) * 1024);
        else if (j < 15) {
          const int nx = it + 1;
          mbar_wait(smem_u32(&s_full[nx % ATT_STAGES]), (nx / ATT_STAGES) & 1);
          scores(sA, sbase + (nx % ATT_STAGES) * ATT_STAGE_BYTES + koff);
        }
        exp_pv(sB, sa, 2 * bp + 1);
      }
      __syncwarp();
      if (lane == 0) mbar_arrive(smem_u32(&s_empty[it % ATT_STAGES]));
    }
    float l[2][2];
    bool bad = false;
#pragma unroll
    for (int m = 0; m < 2; m++) {
      l[m][0] = __shfl_sync(~0u, o[m][2][0], (lane & ~3) | 2);
      l[m][1] = __shfl_sync(~0u, o[m][2][2], (lane & ~3) | 2);
      bad = bad || !(l[m][0] >= 8.271806e-25f && l[m][0] <= 3.0e38f) || !(l[m][1] >= 8.271806e-25f && l[m][1] <= 3.0e38f);
    }
    if (__any_sync(~0u, bad)) attn_exact(h, row0, lane);
    else attn_store(o, l, h, row0, t);
    __syncthreads();
    cur = *(volatile unsigned*)&s_item[round & 1];
    base = it; round++;
    if (cur >= ATT_ITEMS) break;
  }
  TL_END(2);
}

constexpr int REC_THREADS = 384;
constexpr int REC_CTAS = 96;
#define COMM_FIRST 0
#define PATH_SWAP 1
constexpr int INIT_TID = COMM_FIRST ? 96 : 352;
constexpr int SM_WO = 0;
constexpr int SM_X = 57344;
constexpr int SM_KX = SM_X + 2 * 40960;
constexpr int SM_VX = SM_KX + 2 * 8192;
constexpr int SM_QX = SM_VX + 2 * 8192;
constexpr int SM_M = SM_QX + 2 * 8192;
constexpr int SM_G = SM_M + 10240;
constexpr int SM_S = SM_G + 2 * 6144;
constexpr int SM_O = SM_S + 4 * 8 * 56 * 4;
constexpr int SM_P = SM_O + 2048;
constexpr int SM_D = SM_P + 2 * 768;
constexpr int SM_END = SM_D + 4096;
constexpr int SM_WSTAGE = SM_X;
constexpr int REC_SMEM = (SM_WSTAGE + 163840 > SM_END ? SM_WSTAGE + 163840 : SM_END) + 1024;
constexpr float B_SCALE_LOG2E = 0.08838834764831845f * 1.4426950408889634f;

#define XCH_R 3
constexpr uint32_t XCH_EMPTY = 0xFFFFFFFFu;
constexpr int XCH_MBOX_WORDS = REC_CTAS * 2 * 2048  , XCH_MEM_WORDS = XCH_R * 3 * 2048;
__device__ uint32_t g_xch[XCH_MBOX_WORDS + XCH_MEM_WORDS + 2048];
__device__ uint32_t g_sel[REC_CTAS];
__device__ __forceinline__ uint32_t* xch_base() { return (uint32_t*)(((uintptr_t)g_xch + 8191) & ~(uintptr_t)8191); }
__device__ unsigned g_gridbar;

enum { BAR_CMP = 1, BAR_P4 = 2, BAR_S = 5, BAR_XP = 8, BAR_WG1 = 7 };
#define TRMAX(i)
#define TRA(i)
#define TRB(i)
#define TRV(i, val)
#define TR(i)
#define TR1(i)

__device__ __forceinline__ void st_async_v2(uint32_t raddr, uint32_t a, uint32_t b, uint32_t rbar) {
  asm volatile("st.async.weak.shared::cluster.mbarrier::complete_tx::bytes.v2.b32 [%0], {%1, %2}, [%3];" :: "r"(raddr), "r"(a), "r"(b), "r"(rbar) : "memory");
}
__device__ __forceinline__ void bulk_s2c(uint32_t dst, uint32_t src, uint32_t bytes, uint32_t rbar) {
  asm volatile("cp.async.bulk.shared::cluster.shared::cta.mbarrier::complete_tx::bytes [%0], [%1], %2, [%3];" :: "r"(dst), "r"(src), "r"(bytes), "r"(rbar) : "memory");
}
__device__ __forceinline__ uint4 ld_relaxed_v4(const void* p) { uint4 v; asm volatile("ld.relaxed.gpu.global.v4.u32 {%0,%1,%2,%3}, [%4];" : "=r"(v.x), "=r"(v.y), "=r"(v.z), "=r"(v.w) : "l"(p) : "memory"); return v; }
__device__ __forceinline__ uint32_t ld_relaxed(const void* p) { uint32_t v; asm volatile("ld.relaxed.gpu.global.u32 %0, [%1];" : "=r"(v) : "l"(p) : "memory"); return v; }
__device__ __forceinline__ void st_relaxed_v2(void* p, uint32_t a, uint32_t b) { asm volatile("st.relaxed.gpu.global.v2.u32 [%0], {%1,%2};" :: "l"(p), "r"(a), "r"(b) : "memory"); }
__device__ __forceinline__ void st_relaxed_v4(void* p, uint32_t a) { asm volatile("st.relaxed.gpu.global.v4.u32 [%0], {%1,%1,%1,%1};" :: "l"(p), "r"(a) : "memory"); }
__device__ __forceinline__ void st_relaxed(void* p, uint32_t a) { asm volatile("st.relaxed.gpu.global.u32 [%0], %1;" :: "l"(p), "r"(a) : "memory"); }
__device__ __forceinline__ uint32_t lds32(uint32_t a) { uint32_t v; asm volatile("ld.shared.u32 %0, [%1];" : "=r"(v) : "r"(a) : "memory"); return v; }
__device__ __forceinline__ uint2 lds64(uint32_t a) { uint2 v; asm volatile("ld.shared.v2.u32 {%0,%1}, [%2];" : "=r"(v.x), "=r"(v.y) : "r"(a) : "memory"); return v; }
__device__ __forceinline__ void lds128(uint32_t (&r)[4], uint32_t a) { asm volatile("ld.shared.v4.u32 {%0,%1,%2,%3}, [%4];" : "=r"(r[0]), "=r"(r[1]), "=r"(r[2]), "=r"(r[3]) : "r"(a) : "memory"); }
__device__ __forceinline__ void sts64(uint32_t a, uint32_t x, uint32_t y) { asm volatile("st.shared.v2.u32 [%0], {%1,%2};" :: "r"(a), "r"(x), "r"(y) : "memory"); }
__device__ __forceinline__ void sts128(uint32_t a, uint32_t x, uint32_t y, uint32_t z, uint32_t w) { asm volatile("st.shared.v4.u32 [%0], {%1,%2,%3,%4};" :: "r"(a), "r"(x), "r"(y), "r"(z), "r"(w) : "memory"); }
__device__ __forceinline__ void sts32f(uint32_t a, float x) { asm volatile("st.shared.f32 [%0], %1;" :: "r"(a), "f"(x) : "memory"); }
__device__ __forceinline__ float2 lds64f(uint32_t a) { float2 v; asm volatile("ld.shared.v2.f32 {%0,%1}, [%2];" : "=f"(v.x), "=f"(v.y) : "r"(a) : "memory"); return v; }

#define REC_DELAY_A 200
#define REC_ADAPT_UP 0u
#define REC_ADAPT_DN 0u
#define REC_DELAY_OTHER 650
#define REC_DELAY_NR 1200
#define REC_DELAY_C 350
constexpr uint32_t POLL_LIMIT = 1u << 14;
__device__ __forceinline__ uint32_t umax4(const uint4& v) { return max(max(v.x, v.y), max(v.z, v.w)); }
__device__ __forceinline__ void spin_clocks(uint32_t clks) {
  uint32_t t0, t1;
  asm volatile("mov.u32 %0, %%clock;" : "=r"(t0) :: "memory");
  do { asm volatile("mov.u32 %0, %%clock;" : "=r"(t1) :: "memory"); } while (t1 - t0 < clks);
}
#define PROBE_SAMPLES 2
__device__ __forceinline__ uint32_t probe_pair(uint32_t* p) {
  uint32_t best[2];
#pragma unroll
  for (int hf = 0; hf < 2; hf++) {
    uint32_t* q = p + hf * 1024;
    uint32_t v, bst = 0xFFFFFFFFu;
    asm volatile("atom.relaxed.gpu.global.or.b32 %0, [%1], 0;" : "=r"(v) : "l"(q) : "memory");
#pragma unroll 1
    for (int i = 0; i < PROBE_SAMPLES; i++) {
      uint32_t t0, t1;
      q += (v == 0x9E3779B9u);
      asm volatile("mov.u32 %0, %%clock;" : "=r"(t0) :: "memory");
      asm volatile("atom.relaxed.gpu.global.or.b32 %0, [%1], 0;" : "=r"(v) : "l"(q) : "memory");
      if (v == 0x9E3779B9u) q += 0; else asm volatile("" ::: "memory");
      asm volatile("{\n.reg .pred p;\nsetp.eq.u32 p, %1, 0x9E3779B9;\n@p mov.u32 %0, 0;\n@!p mov.u32 %0, %%clock;\n}" : "=r"(t1) : "r"(v) : "memory");
      bst = min(bst, t1 - t0);
    }
    best[hf] = bst;
  }
  return best[1] < best[0];
}
#define PROBE_KIND 1
__device__ __forceinline__ uint32_t probe_sel(uint32_t* p) { return PROBE_KIND == 0 ? 0u : (PROBE_KIND == 1 ? probe_pair(p) : 1u - probe_pair(p)); }
#define PROBE_MODE(f) probe_sel
__device__ __forceinline__ uint32_t mbox_off(int cg, int h, uint32_t sel) { return cg * 4096 + (sel & 1) * 1024 + h * 32; }
__device__ __forceinline__ uint32_t msg_off(uint32_t packed, int buf) { return (packed & 0x0FFFFFFFu) + (buf ? (packed >> 28) << 10 : 0u); }
__device__ __forceinline__ int mbox_buf1(uint32_t sel) { return 2048 + (int)((sel >> 1) & 1) * 1024 - (int)(sel & 1) * 1024; }

struct ScoreAddr { uint32_t lo, lo_stride, hi, hi_mask; };
__device__ __forceinline__ ScoreAddr score_addr(int mt, uint32_t km_addr, uint32_t kx_addr, int lane) {
  ScoreAddr r;
  r.lo = (mt == 0 ? km_addr : kx_addr + (mt == 1 ? 256 : 768)) + lane * 8;
  r.lo_stride = (mt == 0) ? 256 : 1024;
  r.hi = kx_addr + (mt == 1 ? 512 : 0) + lane * 8;
  r.hi_mask = (mt == 2) ? 0u : 0xFFFFFFFFu;
  return r;
}
template <int NCH>
__device__ __forceinline__ void score_finish(const uint2 (&lo)[8], const uint2 (&hi)[8], uint32_t q_addr, int mt, uint32_t s_addr, int lane) {
  float c[NCH][4];
#pragma unroll
  for (int i = 0; i < NCH; i++) { c[i][0] = 0.f; c[i][1] = 0.f; c[i][2] = 0.f; c[i][3] = 0.f; }
#pragma unroll
  for (int k0 = 0; k0 < 8; k0 += NCH) {
    uint2 q[NCH];
#pragma unroll
    for (int i = 0; i < NCH; i++) q[i] = lds64(q_addr + (k0 + i) * 256 + lane * 8);
#pragma unroll
    for (int i = 0; i < NCH; i++) {
      const uint32_t a[4] = {lo[k0 + i].x, hi[k0 + i].x, lo[k0 + i].y, hi[k0 + i].y};
      mma16816(c[i], a, q[i].x, q[i].y);
    }
  }
#pragma unroll
  for (int i = 1; i < NCH; i++) { c[0][0] += c[i][0]; c[0][1] += c[i][1]; c[0][2] += c[i][2]; c[0][3] += c[i][3]; }
  const int g = lane >> 2, t = lane & 3;
  const uint32_t d = s_addr + ((2 * t) * 56 + 16 * mt + g) * 4;
  sts32f(d, c[0][0]); sts32f(d + 56 * 4, c[0][1]); sts32f(d + 32, c[0][2]); sts32f(d + 56 * 4 + 32, c[0][3]);
}
__device__ __forceinline__ void rec_scores(int mt, uint32_t km_addr, uint32_t kx_addr, uint32_t q_addr, uint32_t s_addr, int lane) {
  const ScoreAddr sa = score_addr(mt, km_addr, kx_addr, lane);
  uint2 lo[8], hi[8];
#pragma unroll
  for (int ks = 0; ks < 8; ks++) {
    lo[ks] = lds64(sa.lo + ks * sa.lo_stride);
    hi[ks] = lds64(sa.hi + ks * 1024);
    hi[ks].x &= sa.hi_mask; hi[ks].y &= sa.hi_mask;
  }
  score_finish<4>(lo, hi, q_addr, mt, s_addr, lane);
}
template <int U>
__device__ __forceinline__ void rec_softmax(uint32_t (&pb)[U][5], float (&inv)[U], const uint32_t (&s_addr)[U], const int (&lim)[U], int lane) {
  const int g = lane >> 2, t = lane & 3;
  float v[U][10], m[U];
#pragma unroll
  for (int u = 0; u < U; u++)
#pragma unroll
    for (int i = 0; i < 5; i++) {
      const float2 x = lds64f(s_addr[u] + (g * 56 + 8 * i + 2 * t) * 4);
      v[u][2 * i] = (8 * i + 2 * t <= lim[u]) ? x.x : -INFINITY;
      v[u][2 * i + 1] = (8 * i + 2 * t + 1 <= lim[u]) ? x.y : -INFINITY;
    }
#pragma unroll
  for (int u = 0; u < U; u++)
    m[u] = fmaxf(fmaxf(fmaxf(fmaxf(v[u][0], v[u][1]), fmaxf(v[u][2], v[u][3])), fmaxf(fmaxf(v[u][4], v[u][5]), fmaxf(v[u][6], v[u][7]))), fmaxf(v[u][8], v[u][9]));
#pragma unroll
  for (int u = 0; u < U; u++) m[u] = fmaxf(m[u], __shfl_xor_sync(~0u, m[u], 1));
#pragma unroll
  for (int u = 0; u < U; u++) m[u] = fmaxf(m[u], __shfl_xor_sync(~0u, m[u], 2)) * B_SCALE_LOG2E;
#pragma unroll
  for (int u = 0; u < U; u++) {
#pragma unroll
    for (int i = 0; i < 10; i++) v[u][i] = ex2f(fmaf(v[u][i], B_SCALE_LOG2E, -m[u]));
#pragma unroll
    for (int i = 0; i < 5; i++) pb[u][i] = pack_bf16(v[u][2 * i], v[u][2 * i + 1]);
  }
#pragma unroll
  for (int u = 0; u < U; u++) {
    float x[5];
#pragma unroll
    for (int i = 0; i < 5; i++) x[i] = bf16lo(pb[u][i]) + bf16hi(pb[u][i]);
    inv[u] = ((x[0] + x[1]) + (x[2] + x[3])) + x[4];
  }
#pragma unroll
  for (int u = 0; u < U; u++) inv[u] += __shfl_xor_sync(~0u, inv[u], 1);
#pragma unroll
  for (int u = 0; u < U; u++) { inv[u] += __shfl_xor_sync(~0u, inv[u], 2); asm("rcp.approx.ftz.f32 %0, %0;" : "+f"(inv[u])); }
}
__device__ __forceinline__ void rec_pv(uint32_t& o0, uint32_t& o1, uint2 vm, const uint2 (&vx)[4], const uint32_t (&pb)[5], float ia, float ib) {
  float c[4] = {0.f, 0.f, 0.f, 0.f}, e[4] = {0.f, 0.f, 0.f, 0.f};
  { const uint32_t a[4] = {vx[1].x, vx[1].y, vx[2].x, vx[2].y}; mma16816(e, a, pb[2], pb[3]); }
  { const uint32_t a[4] = {vx[3].x, vx[3].y, 0u, 0u}; mma16816(c, a, pb[4], 0u); }
  { const uint32_t a[4] = {vm.x, vm.y, vx[0].x, vx[0].y}; mma16816(c, a, pb[0], pb[1]); }
  o0 = movmatrix_t(pack_bf16((c[0] + e[0]) * ia, (c[1] + e[1]) * ib));
  o1 = movmatrix_t(pack_bf16((c[2] + e[2]) * ia, (c[3] + e[3]) * ib));
}

template <int NT>
__device__ __forceinline__ void rec_p4(uint32_t wo0, uint32_t wo1, uint32_t o_addr, uint32_t dst_addr, uint32_t* xb, int buf, int bar_id) {
  uint32_t a[NT][4][4];
#pragma unroll
  for (int i = 0; i < 4; i++) { lds128(a[0][i], wo0 + i * 512); if (NT == 2) lds128(a[NT - 1][i], wo1 + i * 512); }
  bar_sync(bar_id, 256);
  float c[NT][2][4];
#pragma unroll
  for (int q = 0; q < NT; q++)
#pragma unroll
    for (int i = 0; i < 2; i++) { c[q][i][0] = 0.f; c[q][i][1] = 0.f; c[q][i][2] = 0.f; c[q][i][3] = 0.f; }
#pragma unroll
  for (int i = 0; i < 4; i++) {
    const uint2 ob = lds64(o_addr + i * 256);
#pragma unroll
    for (int q = 0; q < NT; q++) mma16816(c[q][i & 1], a[q][i], ob.x, ob.y);
  }
#pragma unroll
  for (int i = 0; i < 4; i++) { lds128(a[0][i], wo0 + (4 + i) * 512); if (NT == 2) lds128(a[NT - 1][i], wo1 + (4 + i) * 512); }
  uint32_t dd[NT][2];
#pragma unroll
  for (int q = 0; q < NT; q++) { dd[q][0] = msg_off(lds32(dst_addr + (q * 2) * 1024), buf); dd[q][1] = msg_off(lds32(dst_addr + (q * 2 + 1) * 1024), buf); }
#pragma unroll
  for (int i = 0; i < 4; i++) {
    const uint2 ob = lds64(o_addr + (4 + i) * 256);
#pragma unroll
    for (int q = 0; q < NT; q++) mma16816(c[q][i & 1], a[q][i], ob.x, ob.y);
  }
#pragma unroll
  for (int q = 0; q < NT; q++) {
    st_relaxed(xb + dd[q][0], pack_bf16(c[q][0][0] + c[q][1][0], c[q][0][1] + c[q][1][1]));
    st_relaxed(xb + dd[q][1], pack_bf16(c[q][0][2] + c[q][1][2], c[q][0][3] + c[q][1][3]));
  }
}

__global__ void __cluster_dims__(3, 1, 1) __launch_bounds__(REC_THREADS, 1)
rec_kernel(const __grid_constant__ CUtensorMap tmWq, const __grid_constant__ CUtensorMap tmWk, const __grid_constant__ CUtensorMap tmWv,
           const __grid_constant__ CUtensorMap tmWo, const __grid_constant__ CUtensorMap tmX, const bf16* __restrict__ mem0) {
  extern __shared__ uint8_t smem_raw[];
  const uint32_t sb = (smem_u32(smem_raw) + 1023) & ~1023u;
  __shared__ __align__(8) uint64_t s_bar[15];
  __shared__ uint32_t s_probe[16];
  const uint32_t B_W = smem_u32(&s_bar[10])  , B_WO = smem_u32(&s_bar[1]), B_M = smem_u32(&s_bar[2]), B_G = smem_u32(&s_bar[3]);
  const uint32_t B_KV = smem_u32(&s_bar[4])  , B_XF = smem_u32(&s_bar[6])  , B_XE = smem_u32(&s_bar[8])  ;
  const int tid = threadIdx.x, warp = tid >> 5, lane = tid & 31;
  uint32_t role; asm("mov.u32 %0, %%cluster_ctarank;" : "=r"(role));
  const int h = blockIdx.x / 3;
  TL_START(0);
  const int tile0 = (role == 0) ? 0 : (role == 1 ? 14 : 27), ntile = (role == 0) ? 14 : 13;
  if (lane == 0) {
    uint32_t* const xb0 = xch_base();
    for (int i = COMM_FIRST ? (warp + 8) % 12 : warp; i < 3 * XCH_R + 2; i += 12)
      s_probe[i] = probe_sel(i < 3 * XCH_R ? xb0 + XCH_MBOX_WORDS + i * 2048 + 1000 : xb0 + (blockIdx.x * 2 + (i - 3 * XCH_R)) * 2048 + 1000);
  }
  __syncwarp();
  if (tid == INIT_TID) {
    for (int i = 0; i < 5; i++) mbar_init(B_W + 8 * i, 1);
    mbar_init(B_WO, 1); mbar_init(B_M, 4); mbar_init(B_G, 9);
    mbar_init(B_KV, 1); mbar_init(B_KV + 8, 1); mbar_init(B_XF, 1); mbar_init(B_XF + 8, 1); mbar_init(B_XE, 3); mbar_init(B_XE + 8, 3);
    fence_mbar_init();
  }
  __syncthreads();
  if (tid == INIT_TID) {
    const CUtensorMap* tw = (role == 0) ? &tmWq : (role == 1 ? &tmWk : &tmWv);
    mbar_expect_tx(B_WO, 7 * 8192);
    for (int b = 0; b < 7; b++) tma_load_2d(sb + SM_WO + b * 8192, &tmWo, tile0 * 16 + b * 32, h * 128, B_WO);
    for (int c = 0; c < 10; c++) {
      if ((c & 1) == 0) mbar_expect_tx(B_W + 8 * (c >> 1), 32768);
      tma_load_2d(sb + SM_WSTAGE + c * 16384, tw, h * 128, c * 64, B_W + 8 * (c >> 1));
      tma_load_2d(sb + SM_WSTAGE + c * 16384 + 8192, tw, h * 128 + 64, c * 64, B_W + 8 * (c >> 1));
    }
  }
  __syncwarp();
  TL_END(6);
  asm volatile("barrier.cluster.arrive.release.aligned;\nbarrier.cluster.wait.acquire.aligned;" ::: "memory");

  if (COMM_FIRST ? (warp < 4) : (warp >= 8)) {
    asm volatile("setmaxnreg.dec.sync.aligned.u32 56;");
    uint32_t tid_c; asm volatile("mov.u32 %0, %%tid.x;" : "=r"(tid_c));
    const int ct = (int)tid_c - (COMM_FIRST ? 0 : 256), cw = ct >> 5, lane = ct & 31;
    const bool red = blockIdx.x < 80;
    uint32_t* const xb = xch_base();
    const uint32_t mysel = s_probe[3 * XCH_R] | (s_probe[3 * XCH_R + 1] << 1);
    const uint32_t probe_sa = smem_u32(s_probe);
    uint32_t* const mbw = xb + mbox_off(blockIdx.x, 0, mysel) + lane;
    uint4* const mb0 = (uint4*)(xb + mbox_off(blockIdx.x, 8 * cw, mysel)) + lane;
    auto buf1_words = [&]() { return 2048 + (int)lds32(probe_sa + (3 * XCH_R + 1) * 4) * 1024 - (int)lds32(probe_sa + 3 * XCH_R * 4) * 1024; };
    const uint32_t pub_off = XCH_MBOX_WORDS + ((blockIdx.x * 32) >> 10) * 2048 + ((blockIdx.x * 32 + lane) & 1023);
    const uint4 empty4 = make_uint4(XCH_EMPTY, XCH_EMPTY, XCH_EMPTY, XCH_EMPTY);
    if (red) {
      { const int mb1 = buf1_words() / 4; mb0[0] = empty4; mb0[32] = empty4; mb0[mb1] = empty4; mb0[mb1 + 32] = empty4; }
      if (cw < 2) xb[pub_off + 1 * 6144 + cw * 1024] = XCH_EMPTY;
    }
    if (ct == 0) g_sel[blockIdx.x] = mysel;
    __threadfence();
    bar_sync(3, 128);
    if (ct == 0) {
      const unsigned old = atomicAdd(&g_gridbar, 1u);
      const unsigned target = (old / REC_CTAS + 1) * REC_CTAS;
      uint32_t n = 0;
      while ((int)(ld_relaxed(&g_gridbar) - target) < 0) { if (++n > (1u << 20)) { g_timeout_flag = 3; break; } }
      __threadfence();
    }
    auto load_x = [&](int seg) {
      const int xc0 = (role == 0) ? 0 : (role == 1 ? 4 : 7), xc1 = (role == 0) ? 4 : (role == 1 ? 7 : 10);
      const uint32_t fb = B_XF + 8 * (seg & 1);
      mbar_expect_tx(fb, 40960);
      for (int c = xc0; c < xc1; c++) tma_load_3d_mc(sb + SM_X + (seg & 1) * 40960 + c * 4096, &tmX, 0, seg * 32, c, fb, (uint16_t)7);
    };
    uint4 m0v[5];
#pragma unroll
    for (int i = 0; i < 5; i++) { const int v = ct + i * 128; m0v[i] = *(const uint4*)(mem0 + (v & 7) * DM + (v >> 3) * 8); }
    bar_sync(3, 128);
    bar_sync(4, REC_THREADS);
#pragma unroll
    for (int i = 0; i < 5; i++) sts128(sb + SM_M + (ct + i * 128) * 16, m0v[i].x, m0v[i].y, m0v[i].z, m0v[i].w);
    __syncwarp();
    if (lane == 0) mbar_arrive(B_M);
    asm volatile("barrier.cluster.arrive.release.aligned;\nbarrier.cluster.wait.acquire.aligned;" ::: "memory");
    uint32_t dlyA = red ? REC_DELAY_A : REC_DELAY_NR, dlyC = REC_DELAY_C;
    int slot = 0;
#pragma unroll 1
    for (int s = 0; s < B_NSEG; s++, slot = (slot == XCH_R - 1) ? 0 : slot + 1) {
      if (s > 0) {
        const uint32_t* ms = xb + XCH_MBOX_WORDS + slot * 6144 + ct * 4;
        const uint4* src0 = (const uint4*)(ms + lds32(probe_sa + slot * 12) * 1024);
        const uint4* src1 = (const uint4*)(ms + 2048 + lds32(probe_sa + slot * 12 + 4) * 1024);
        const uint4* src2 = (const uint4*)(ms + 4096 + lds32(probe_sa + slot * 12 + 8) * 1024);
        uint4 v0, v1, v2, v3, v4;
        spin_clocks(dlyA);
        TR(27);
#pragma unroll 1
        v0 = v1 = v2 = v3 = v4 = make_uint4(XCH_EMPTY, XCH_EMPTY, XCH_EMPTY, XCH_EMPTY);
        uint32_t nit = 0;
        for (uint32_t n = 0;; n++) {
          if (umax4(v0) == XCH_EMPTY) v0 = ld_relaxed_v4(src0);
          if (umax4(v1) == XCH_EMPTY) v1 = ld_relaxed_v4(src0 + 128);
          if (umax4(v2) == XCH_EMPTY) v2 = ld_relaxed_v4(src1);
          if (umax4(v3) == XCH_EMPTY) v3 = ld_relaxed_v4(src1 + 128);
          if (umax4(v4) == XCH_EMPTY) v4 = ld_relaxed_v4(src2);
          const uint32_t m = max(max(max(umax4(v0), umax4(v1)), max(umax4(v2), umax4(v3))), umax4(v4));
          if (m != XCH_EMPTY) { nit = n; break; }
          if (n > POLL_LIMIT) { g_timeout_flag = 4; break; }
        }
        {
          const uint32_t mx = __reduce_max_sync(~0u, nit);
          dlyA = mx ? min(dlyA + REC_ADAPT_UP, 4000u) : (dlyA > REC_ADAPT_DN ? dlyA - REC_ADAPT_DN : 0u);
          TRV(26, mx); TRV(21, dlyA);
        }
        const uint32_t dst = sb + SM_M + ct * 16;
        sts128(dst, v0.x, v0.y, v0.z, v0.w); sts128(dst + 2048, v1.x, v1.y, v1.z, v1.w); sts128(dst + 4096, v2.x, v2.y, v2.z, v2.w);
        sts128(dst + 6144, v3.x, v3.y, v3.z, v3.w); sts128(dst + 8192, v4.x, v4.y, v4.z, v4.w);
        __syncwarp();
        if (lane == 0) mbar_arrive(B_M);
        TR(9);
        TRMAX(30);
      }
      if (ct == 0 && s + 2 < B_NSEG) {
        mbar_wait(B_XE + 8 * (s & 1), (s >> 1) & 1);
        load_x(s + 2);
      }
      if (s == B_NSEG - 1) break;
      if (red) {
        if (cw < 2) st_relaxed(xb + pub_off + ((slot + 2) % XCH_R) * 6144 + cw * 1024, XCH_EMPTY);
        if (s > 0) {
          uint4* const old = mb0 + ((s & 1) ? 0 : buf1_words() / 4);
          st_relaxed_v4(old, XCH_EMPTY); st_relaxed_v4(old + 32, XCH_EMPTY);
        }
      }
      asm volatile("fence.acq_rel.gpu;" ::: "memory");
      TR(10);
      bar_sync(BAR_P4, REC_THREADS);
      if (red) {
        if (cw == 0) {
          const uint32_t* const src = mbw + ((s & 1) ? buf1_words() : 0);
          spin_clocks(dlyC);
          TR(11);
          float f[8];
          uint32_t nit = 0;
          const uint4* const src4 = (const uint4*)(src - lane) + lane;
#pragma unroll 1
          for (uint32_t n = 0;; n++) {
            uint4 v[8];
#pragma unroll
            for (int i = 0; i < 8; i++) v[i] = ld_relaxed_v4(src4 + i * 32);
            uint32_t mx = 0;
#pragma unroll
            for (int j = 0; j < 8; j++) f[j] = 0.f;
#pragma unroll
            for (int i = 0; i < 8; i++) {
              mx = max(mx, umax4(v[i]));
              f[0] += bf16lo(v[i].x); f[1] += bf16hi(v[i].x); f[2] += bf16lo(v[i].y); f[3] += bf16hi(v[i].y);
              f[4] += bf16lo(v[i].z); f[5] += bf16hi(v[i].z); f[6] += bf16lo(v[i].w); f[7] += bf16hi(v[i].w);
            }
            if (__all_sync(~0u, mx != XCH_EMPTY)) { nit = n; break; }
            if (n > POLL_LIMIT) { g_timeout_flag = 5; break; }
          }
          dlyC = nit ? min(dlyC + REC_ADAPT_UP, 4000u) : (dlyC > REC_ADAPT_DN ? dlyC - REC_ADAPT_DN : 0u);
          TRV(25, nit); TR(17);
          float e[4];
#pragma unroll
          for (int j = 0; j < 4; j++) {
            const float send = (lane & 16) ? f[j] : f[4 + j], keep = (lane & 16) ? f[4 + j] : f[j];
            e[j] = keep + __shfl_xor_sync(~0u, send, 16);
          }
          float d2[2];
#pragma unroll
          for (int j = 0; j < 2; j++) {
            const float send = (lane & 8) ? e[j] : e[2 + j], keep = (lane & 8) ? e[2 + j] : e[j];
            d2[j] = keep + __shfl_xor_sync(~0u, send, 8);
          }
          const int row = lane >> 2, u = lane & 3;
          const int pc = (row >> 1) * 2 + (u >> 1), q0 = (2 * u) & 3;
          const int l0 = q0 * 8 + pc, l1 = (q0 + 1) * 8 + pc;
          const float x00 = __shfl_sync(~0u, d2[0], l0), x01 = __shfl_sync(~0u, d2[1], l0), x10 = __shfl_sync(~0u, d2[0], l1), x11 = __shfl_sync(~0u, d2[1], l1);
          const uint32_t w = (row & 1) ? pack_bf16(x01, x11) : pack_bf16(x00, x10);
          uint32_t* const pub = xb + pub_off + ((slot + 1) % XCH_R) * 6144;
          st_relaxed(pub, w); st_relaxed(pub + 1024, w);
        } else {
          spin_clocks(dlyC + REC_DELAY_OTHER);
        }
        TR(12);
        TRMAX(29);
      }
    }
  } else {
    asm volatile("setmaxnreg.inc.sync.aligned.u32 224;");
    uint32_t tid_c; asm volatile("mov.u32 %0, %%tid.x;" : "=r"(tid_c));
    const int tid = (int)tid_c - (COMM_FIRST ? 128 : 0), warp = tid >> 5, lane = tid & 31;
    const int g = lane >> 2, t = lane & 3;
    uint32_t* const xb = xch_base();
    uint32_t W[40][4];
    {
      mbar_wait(B_WO, 0);
      TL_END(10);
      uint32_t f[2][8][4];
#pragma unroll
      for (int q = 0; q < 2; q++) {
        const int i = min(warp + 8 * q, 13);
#pragma unroll
        for (int ks = 0; ks < 8; ks++) {
          const int e = ks * 16 + (lane & 7) + ((lane >> 4) & 1) * 8;
          const int ch = (i & 1) * 2 + ((lane >> 3) & 1);
          ldsm_x4_t(f[q][ks], sb + SM_WO + (i >> 1) * 8192 + e * 64 + ((ch ^ ((e >> 1) & 3)) << 4));
        }
      }
      bar_sync(BAR_CMP, 256);
#pragma unroll
      for (int q = 0; q < 2; q++) {
        const int i = warp + 8 * q;
        if (i < 14) {
#pragma unroll
          for (int ks = 0; ks < 8; ks++) sts128(sb + SM_WO + (i * 8 + ks) * 512 + lane * 16, f[q][ks][0], f[q][ks][1], f[q][ks][2], f[q][ks][3]);
        }
      }
    }
#pragma unroll
    for (int gq = 0; gq < 5; gq++) {
      mbar_wait(B_W + 8 * gq, 0);
      if (gq == 4) { TL_END(7); }
#pragma unroll
      for (int k8 = 0; k8 < 8; k8++) {
        const int ks = gq * 8 + k8;
        const int k = (ks & 3) * 16 + (lane & 7) + ((lane >> 4) & 1) * 8;
        const int ch = (warp & 3) * 2 + ((lane >> 3) & 1);
        ldsm_x4_t(W[ks], sb + SM_WSTAGE + (ks >> 2) * 16384 + (warp >> 2) * 8192 + k * 128 + ((ch ^ (k & 7)) << 4));
      }
      if (gq == 1 || gq == 2) {
        bar_sync(BAR_CMP, 256);
        if (tid == 0) {
          const int seg = gq - 1;
          mbar_expect_tx(B_XF + 8 * seg, 40960);
          for (int c = 0; c < 10; c++) tma_load_3d(sb + SM_X + seg * 40960 + c * 4096, &tmX, 0, seg * 32, c, B_XF + 8 * seg);
        }
        __syncwarp();
      }
    }
    bar_sync(4, REC_THREADS);
    asm volatile("barrier.cluster.arrive.release.aligned;\nbarrier.cluster.wait.acquire.aligned;" ::: "memory");

    const uint32_t peer0 = (role + 1) % 3, peer1 = (role + 2) % 3;
    const int pw = PATH_SWAP ? (warp ^ 4) : warp;
    const int mytile0 = (pw >= 4) ? pw - 4 : 8 + pw, mytile1 = (pw >= 4) ? pw : 12 + pw;
    const bool has_tile1 = mytile1 < ntile;
    float d[16];
    auto bulk_issue = [&](int seg) {
      const int b = seg & 1;
      if (seg < B_NSEG) mbar_wait(B_XF + 8 * b, (seg >> 1) & 1);
      __syncwarp();
      const uint64_t dx = make_desc(sb + SM_X, 16, 1024, 1) + (uint64_t)(b * (40960 >> 4));
      wgmma_fence();
#pragma unroll
      for (int ks = 0; ks < 40; ks++) wgmma_rs_n32(d, W[ks], dx + (ks >> 2) * 256 + (ks & 3) * 2, ks > 0);
      wgmma_commit();
    };
    auto bulk_convert = [&](int seg) {
      const int b = seg & 1;
      const uint32_t dst = sb + (role == 0 ? SM_QX + warp * 256 : (role == 1 ? SM_KX : SM_VX) + warp * 1024) + b * 8192 + lane * 8;
      const uint32_t jstr = (role == 0) ? 2048 : 256;
#pragma unroll
      for (int j = 0; j < 4; j++) {
        uint32_t x0 = pack_bf16(d[4 * j], d[4 * j + 1]), x1 = pack_bf16(d[4 * j + 2], d[4 * j + 3]);
        if (role != 2) { x0 = movmatrix_t(x0); x1 = movmatrix_t(x1); }
        sts64(dst + j * jstr, x0, x1);
      }
      fence_proxy_async();
    };
    auto bulk_send = [&](int seg) {
      const int b = seg & 1;
      if (tid >= 32 && tid < 35) mbar_arrive_cluster(mapa_u32(B_XE + 8 * b, tid - 32));
      if (tid == 0) {
        mbar_expect_tx(B_KV + 8 * b, role == 0 ? 16384 : 8192 + 2048);
        if (role != 0) {
          const uint32_t src = sb + (role == 1 ? SM_KX : SM_VX) + b * 8192;
          bulk_s2c(mapa_u32(src, peer0), src, 8192, mapa_u32(B_KV + 8 * b, peer0));
          bulk_s2c(mapa_u32(src, peer1), src, 8192, mapa_u32(B_KV + 8 * b, peer1));
        } else {
          const uint32_t src = sb + SM_QX + b * 8192;
          bulk_s2c(mapa_u32(src + 2 * 2048, 1), src + 2 * 2048, 2048, mapa_u32(B_KV + 8 * b, 1));
          bulk_s2c(mapa_u32(src + 3 * 2048, 2), src + 3 * 2048, 2048, mapa_u32(B_KV + 8 * b, 2));
        }
      }
    };
    TL_END(8);
    bulk_issue(0);
    wgmma_wait<0>();
    reg_fence(d);
    bulk_convert(0);
    bar_sync(BAR_CMP, 256);
    bulk_send(0);
    TL_END(9);
    mbar_wait(B_M, 0);
    TL_END(5);
#pragma unroll
    for (int q = 0; q < 2; q++)
#pragma unroll
      for (int hf = 0; hf < 2; hf++) {
        const int tile = tile0 + min(q ? mytile1 : mytile0, ntile - 1);
        const int cg = tile * 2 + hf;
        const uint32_t sel = ld_relaxed(&g_sel[cg]);
        const uint32_t pk = (mbox_off(cg, h, sel) + t * 8 + g) | ((uint32_t)(mbox_buf1(sel) >> 10) << 28);
        asm volatile("st.shared.u32 [%0], %1;" :: "r"(sb + SM_D + (q * 2 + hf) * 1024 + tid * 4), "r"(pk) : "memory");
      }

#pragma unroll 1
    for (int s = 0; s < B_NSEG; s++) {
      const int b = s & 1;
      const uint32_t sG = sb + SM_G + b * 6144, sKX = sb + SM_KX + b * 8192, sVX = sb + SM_VX + b * 8192;
      if (tid == 0) mbar_expect_tx(B_G, 4096);
      TR(0);
      mbar_wait(B_M, s & 1);
      TR(1);
      {
        float c[4][4];
#pragma unroll
        for (int i = 0; i < 4; i++) { c[i][0] = 0.f; c[i][1] = 0.f; c[i][2] = 0.f; c[i][3] = 0.f; }
#pragma unroll
        for (int i = 0; i < 20; i++) {
          uint32_t mb[4];
          ldsm_x4(mb, sb + SM_M + i * 512 + lane * 16);
          mma16816(c[(2 * i) & 3], W[2 * i], mb[0], mb[1]);
          mma16816(c[(2 * i + 1) & 3], W[2 * i + 1], mb[2], mb[3]);
        }
        uint32_t x0 = pack_bf16(c[0][0] + c[1][0] + c[2][0] + c[3][0], c[0][1] + c[1][1] + c[2][1] + c[3][1]);
        uint32_t x1 = pack_bf16(c[0][2] + c[1][2] + c[2][2] + c[3][2], c[0][3] + c[1][3] + c[2][3] + c[3][3]);
        if (role != 2) { x0 = movmatrix_t(x0); x1 = movmatrix_t(x1); }
        const uint32_t off = sG + role * 2048 + warp * 256 + lane * 8;
        st_async_v2(mapa_u32(off, peer0), x0, x1, mapa_u32(B_G, peer0));
        st_async_v2(mapa_u32(off, peer1), x0, x1, mapa_u32(B_G, peer1));
        sts64(off, x0, x1);
        __syncwarp();
        if (lane == 0) mbar_arrive(B_G);
      }
      TR(2);
      mbar_wait(B_KV + 8 * b, (s >> 1) & 1);
      TR(3);
      const bool last = (s == B_NSEG - 1);
      if (pw < 4) {
        uint2 vx[2][4], vm[2];
#pragma unroll
        for (int m = 0; m < 2; m++)
#pragma unroll
          for (int j = 0; j < 4; j++) vx[m][j] = lds64(sVX + (2 * pw + m) * 1024 + j * 256 + lane * 8);
        mbar_wait(B_G, s & 1);
        TRA(4);
        if (!last) {
#pragma unroll
          for (int m = 0; m < 2; m++) vm[m] = lds64(sG + 2 * 2048 + (2 * pw + m) * 256 + lane * 8);
          bar_sync(BAR_S, 224);
          { const float dmy = lds64f(sb + SM_S).x; if (dmy == 1.2345e-30f) g_timeout_flag = 9; }
          TRA(14);
          uint32_t pb[1][5]; float inv[1];
          { const uint32_t sa[1] = {sb + SM_S}; const int lim[1] = {39}; rec_softmax<1>(pb, inv, sa, lim, lane); }
          const float ia = __shfl_sync(~0u, inv[0], 8 * t), ib = __shfl_sync(~0u, inv[0], 8 * t + 4);
#pragma unroll
          for (int m = 0; m < 2; m++) {
            uint32_t o0, o1;
            rec_pv(o0, o1, vm[m], vx[m], pb[0], ia, ib);
            sts64(sb + SM_O + (2 * pw + m) * 256 + lane * 8, o0, o1);
          }
          TRA(13);
          const uint32_t wo0 = sb + SM_WO + mytile0 * 4096 + lane * 16, wo1 = sb + SM_WO + mytile1 * 4096 + lane * 16;
          if (has_tile1) rec_p4<2>(wo0, wo1, sb + SM_O + lane * 8, sb + SM_D + tid * 4, xb, b, BAR_CMP);
          else rec_p4<1>(wo0, wo1, sb + SM_O + lane * 8, sb + SM_D + tid * 4, xb, b, BAR_CMP);
        }
      } else {
        const int mt = pw - 4;
        if (!last && mt < 3) {
          const ScoreAddr sa = score_addr(mt, sG + 2048, sKX, lane);
          uint2 lo[8], hi[8];
#pragma unroll
          for (int ks = 0; ks < 8; ks++) { hi[ks] = lds64(sa.hi + ks * 1024); hi[ks].x &= sa.hi_mask; hi[ks].y &= sa.hi_mask; }
          mbar_wait(B_G, s & 1);
#pragma unroll
          for (int ks = 0; ks < 8; ks++) lo[ks] = lds64(sa.lo + ks * sa.lo_stride);
          score_finish<4>(lo, hi, sG, mt, sb + SM_S, lane);
          TRB(15);
          bar_arrive(BAR_S, 224);
        } else {
          mbar_wait(B_G, s & 1);
        }
        if (pw != 6) {
          const int xmt = (pw == 7) ? 0 : pw - 3, j0 = (role == 0) ? 0 : role + 1;
          const ScoreAddr sa = score_addr(xmt, sG + 2048, sKX, lane);
          const uint32_t qa = sb + SM_QX + b * 8192 + j0 * 2048 + lane * 8;
          float c[2][2][4];
#pragma unroll
          for (int u = 0; u < 2; u++)
#pragma unroll
            for (int i = 0; i < 2; i++) { c[u][i][0] = 0.f; c[u][i][1] = 0.f; c[u][i][2] = 0.f; c[u][i][3] = 0.f; }
#pragma unroll
          for (int k0 = 0; k0 < 8; k0 += 4) {
            uint2 lo[4], hi[4];
#pragma unroll
            for (int i = 0; i < 4; i++) {
              lo[i] = lds64(sa.lo + (k0 + i) * sa.lo_stride);
              hi[i] = lds64(sa.hi + (k0 + i) * 1024);
              hi[i].x &= sa.hi_mask; hi[i].y &= sa.hi_mask;
            }
#pragma unroll
            for (int u = 0; u < 2; u++) {
              if (u == 0 || role == 0) {
#pragma unroll
                for (int i = 0; i < 4; i++) {
                  const uint2 q = lds64(qa + u * 2048 + (k0 + i) * 256);
                  const uint32_t a[4] = {lo[i].x, hi[i].x, lo[i].y, hi[i].y};
                  mma16816(c[u][i & 1], a, q.x, q.y);
                }
              }
            }
          }
#pragma unroll
          for (int u = 0; u < 2; u++) {
            if (u == 0 || role == 0) {
              const uint32_t dd = sb + SM_S + (1 + u) * (8 * 56 * 4) + ((2 * t) * 56 + 16 * xmt + g) * 4;
              sts32f(dd, c[u][0][0] + c[u][1][0]); sts32f(dd + 56 * 4, c[u][0][1] + c[u][1][1]);
              sts32f(dd + 32, c[u][0][2] + c[u][1][2]); sts32f(dd + 56 * 4 + 32, c[u][0][3] + c[u][1][3]);
            }
          }
        }
        TRB(16);
        if (!last) rec_p4<2>(sb + SM_WO + mytile0 * 4096 + lane * 16, sb + SM_WO + mytile1 * 4096 + lane * 16, sb + SM_O + lane * 8, sb + SM_D + tid * 4, xb, b, BAR_CMP);
      }
      TRMAX(28);
      if (!last) bar_arrive(BAR_P4, REC_THREADS);
      TR(6);
      TR1(16);
      {
        const uint32_t sQX = sb + SM_QX + b * 8192;
        const int nu = (role == 0) ? 2 : 1, j0 = (role == 0) ? 0 : role + 1;
        if (last) bar_sync(BAR_CMP, 256);
        if (warp < 4) {
          bulk_issue(s + 1);

          wgmma_wait<0>();
          reg_fence(d);
          if (!last) bulk_convert(s + 1);

        } else {
          if (warp - 4 < nu) {
            const int u = warp - 4;
            uint32_t pb[1][5]; float inv[1];
            const uint32_t sa[1] = {sb + SM_S + (1 + u) * (8 * 56 * 4)};
            const int lim[1] = {8 + 8 * (j0 + u) + g};
            rec_softmax<1>(pb, inv, sa, lim, lane);
#pragma unroll
            for (int i = 0; i < 5; i++) asm volatile("st.shared.u32 [%0], %1;" :: "r"(sb + SM_P + u * 768 + i * 128 + lane * 4), "r"(pb[0][i]) : "memory");
            if (t == 0) sts32f(sb + SM_P + u * 768 + 640 + g * 4, inv[0]);
          }
          __syncwarp();
          bulk_issue(s + 1);
          TR1(19);
          wgmma_wait<0>();
          reg_fence(d);
          TR1(20);
          if (!last) bulk_convert(s + 1);
          TR1(21);
        }
        bar_sync(BAR_CMP, 256);
        if (!last) bulk_send(s + 1);
        TR(7);
        uint2 vx[4];
#pragma unroll
        for (int j = 0; j < 4; j++) vx[j] = lds64(sVX + warp * 1024 + j * 256 + lane * 8);
        const uint2 vm = lds64(sG + 2 * 2048 + warp * 256 + lane * 8);
#pragma unroll
        for (int u = 0; u < 2; u++) {
          if (u < nu) {
            uint32_t pb[5];
#pragma unroll
            for (int i = 0; i < 5; i++) pb[i] = lds32(sb + SM_P + u * 768 + i * 128 + lane * 4);
            const float2 iv = lds64f(sb + SM_P + u * 768 + 640 + t * 8);
            uint32_t o0, o1;
            rec_pv(o0, o1, vm, vx, pb, iv.x, iv.y);
            const uint32_t d = sQX + (u * 8 + g) * 272 + (warp * 16 + 2 * t) * 2;
            asm volatile("st.shared.u32 [%0], %1;" :: "r"(d), "r"(o0) : "memory");
            asm volatile("st.shared.u32 [%0], %1;" :: "r"(d + 16), "r"(o1) : "memory");
          }
        }
        bar_sync(BAR_CMP, 256);
        if (tid < 128 * nu) {
          const int r = tid >> 4, c = tid & 15;
          uint32_t v[4];
          lds128(v, sQX + r * 272 + c * 16);
          *(uint4*)(g_oB + (size_t)(s * 32 + 8 * j0 + r) * B_HD + h * 128 + c * 8) = make_uint4(v[0], v[1], v[2], v[3]);
        }
      }
      TR(8);
    }
  }
  TL_END(0);
  asm volatile("barrier.cluster.arrive.release.aligned;\nbarrier.cluster.wait.acquire.aligned;" ::: "memory");
}

#define HOST_SETUP_EXTRA cudaFuncSetAttribute(rec_kernel, cudaFuncAttributeMaxDynamicSharedMemorySize, REC_SMEM);

typedef CUresult (*PFN_encodeTiled)(CUtensorMap*, CUtensorMapDataType, cuuint32_t, void*, const cuuint64_t*, const cuuint64_t*,
                                    const cuuint32_t*, const cuuint32_t*, CUtensorMapInterleave, CUtensorMapSwizzle,
                                    CUtensorMapL2promotion, CUtensorMapFloatOOBfill);
static PFN_encodeTiled g_encode = nullptr;

static CUtensorMap make_map(const void* base, int rank, const uint64_t* dims, const uint64_t* strides_bytes, const uint32_t* box, CUtensorMapSwizzle swz) {
  CUtensorMap m;
  cuuint64_t d[5], s[5]; cuuint32_t b[5], e[5];
  for (int i = 0; i < rank; i++) { d[i] = dims[i]; b[i] = box[i]; e[i] = 1; }
  for (int i = 0; i + 1 < rank; i++) s[i] = strides_bytes[i];
  CUresult r = g_encode(&m, CU_TENSOR_MAP_DATA_TYPE_BFLOAT16, rank, const_cast<void*>(base), d, s, b, e, CU_TENSOR_MAP_INTERLEAVE_NONE, swz,
                        CU_TENSOR_MAP_L2_PROMOTION_L2_256B, CU_TENSOR_MAP_FLOAT_OOB_FILL_NONE);
  if (r != CUDA_SUCCESS) fprintf(stderr, "cuTensorMapEncodeTiled failed: %d\n", (int)r);
  return m;
}
static CUtensorMap map2d(const void* base, uint64_t inner, uint64_t outer, uint64_t pitch_bytes, uint32_t box_inner, uint32_t box_outer, CUtensorMapSwizzle swz) {
  uint64_t dims[2] = {inner, outer}, st[1] = {pitch_bytes}; uint32_t box[2] = {box_inner, box_outer};
  return make_map(base, 2, dims, st, box, swz);
}
template <typename T> static void* sym_addr(const T& sym) { void* p = nullptr; cudaGetSymbolAddress(&p, sym); return p; }

struct HostState {
  bool init;
  const void* in_ptr[10];
  CUtensorMap a_x, a_wqkv, a_k, a_v, a_att, a_wo, b_o, b_wo, r_wq, r_wk, r_wv, r_wo, r_x;
  cudaStream_t s2;
  cudaEvent_t ev_fork, ev_join;
};
static HostState g_hs;

constexpr int QKV_STAGES = 6, OUTA_STAGES = 6, OUTB_STAGES = 6;
constexpr int QKV_SMEM = QKV_STAGES * GEMM_STAGE + 1024;
constexpr int OUTA_SMEM = OUTA_STAGES * GEMM_STAGE + 1024;
constexpr int OUTB_SMEM = OUTB_STAGES * GEMM_STAGE + 1024;

static void host_setup(void* const* d_in) {
  HostState& H = g_hs;
  if (!g_encode) {
    void* fn = nullptr; cudaDriverEntryPointQueryResult qr;
    cudaGetDriverEntryPoint("cuTensorMapEncodeTiled", &fn, cudaEnableDefault, &qr);
    g_encode = (PFN_encodeTiled)fn;
  }
  bool same = H.init;
  for (int i = 0; i < 9; i++) same = same && (H.in_ptr[i] == d_in[i]);
  if (same) return;
  for (int i = 0; i < 9; i++) H.in_ptr[i] = d_in[i];
  const CUtensorMapSwizzle S128 = CU_TENSOR_MAP_SWIZZLE_128B, S64 = CU_TENSOR_MAP_SWIZZLE_64B;
  H.a_x = map2d(d_in[0], DM, S_LEN, DM * 2, 64, 128, S128);
  H.a_wqkv = map2d(d_in[1], 3 * DM, DM, 3 * DM * 2, 32, 64, S64);
  H.a_k = map2d(sym_addr(g_Kp), 32, A_H * S_LEN, 64, 32, 128, S64);
  H.a_v = map2d(sym_addr(g_Vt), S_LEN, A_H * 24, S_LEN * 2, 64, 24, S128);
  H.a_att = map2d(sym_addr(g_aA), DM, S_LEN, DM * 2, 64, 128, S128);
  H.a_wo = map2d(d_in[2], DM, DM, DM * 2, 32, 64, S64);
  H.b_o = map2d(sym_addr(g_oB), B_HD, S_LEN, B_HD * 2, 64, 128, S128);
  H.b_wo = map2d(d_in[8], DM, B_HD, DM * 2, 32, 64, S64);
  H.r_wq = map2d(d_in[5], B_HD, DM, B_HD * 2, 64, 64, S128);
  H.r_wk = map2d(d_in[6], B_HD, DM, B_HD * 2, 64, 64, S128);
  H.r_wv = map2d(d_in[7], B_HD, DM, B_HD * 2, 64, 64, S128);
  H.r_wo = map2d(d_in[8], DM, B_HD, DM * 2, 32, 128, S64);
  {
    uint64_t dims[3] = {64, (uint64_t)S_LEN, 10}, st[2] = {DM * 2, 128}; uint32_t box[3] = {64, 32, 1};
    H.r_x = make_map(d_in[3], 3, dims, st, box, S128);
  }
  if (!H.init) {
    cudaFuncSetAttribute(gemm_kernel<EPI_QKV, QKV_STAGES, 1>, cudaFuncAttributeMaxDynamicSharedMemorySize, QKV_SMEM);
    cudaFuncSetAttribute(gemm_kernel<EPI_OUT, OUTA_STAGES, 1>, cudaFuncAttributeMaxDynamicSharedMemorySize, OUTA_SMEM);
    cudaFuncSetAttribute(gemm_kernel<EPI_OUT_SK, OUTB_STAGES, 1>, cudaFuncAttributeMaxDynamicSharedMemorySize, OUTB_SMEM);
    cudaFuncSetAttribute(attnA_kernel, cudaFuncAttributeMaxDynamicSharedMemorySize, ATT_SMEM);
    HOST_SETUP_EXTRA
  }
  H.init = true;
}

static void launch_A(cudaStream_t st, bf16* out) {
  HostState& H = g_hs;
  gemm_kernel<EPI_QKV, QKV_STAGES, 1><<<dim3(12, 16), GEMM_THREADS, QKV_SMEM, st>>>(H.a_x, H.a_wqkv, DM, nullptr, 0);
  attnA_kernel<<<132 * 4, 128, ATT_SMEM, st>>>(H.a_k, H.a_v);
  gemm_kernel<EPI_OUT, OUTA_STAGES, 1><<<dim3(4, 16), GEMM_THREADS, OUTA_SMEM, st>>>(H.a_att, H.a_wo, DM, out, 0);
}
static void launch_Bout(cudaStream_t st, bf16* out) {
  HostState& H = g_hs;
  cudaLaunchConfig_t cfg = {};
  cfg.gridDim = dim3(4, 16, 2); cfg.blockDim = dim3(GEMM_THREADS); cfg.dynamicSmemBytes = OUTB_SMEM; cfg.stream = st;
  cudaLaunchAttribute at[1];
  at[0].id = cudaLaunchAttributeClusterDimension; at[0].val.clusterDim.x = 1; at[0].val.clusterDim.y = 1; at[0].val.clusterDim.z = 2;
  cfg.attrs = at; cfg.numAttrs = 1;
  cudaLaunchKernelEx(&cfg, gemm_kernel<EPI_OUT_SK, OUTB_STAGES, 1>, H.b_o, H.b_wo, (int)B_HD, out, (int)DM);
}

static void launch_rec(cudaStream_t st, const bf16* mem0) {
  HostState& H = g_hs;
  rec_kernel<<<REC_CTAS, REC_THREADS, REC_SMEM, st>>>(H.r_wq, H.r_wk, H.r_wv, H.r_wo, H.r_x, mem0);
}

extern "C" void kernel_launch(void* const* d_in, const int* in_sizes, int n_in, void* d_out, int out_size) {
  (void)in_sizes; (void)n_in; (void)out_size;
  host_setup(d_in);
  HostState& H = g_hs;
  cudaStream_t st = cudaStreamPerThread;
  if (!H.s2) {
    cudaStreamCreateWithFlags(&H.s2, cudaStreamNonBlocking);
    cudaEventCreateWithFlags(&H.ev_fork, cudaEventDisableTiming);
    cudaEventCreateWithFlags(&H.ev_join, cudaEventDisableTiming);
  }
  cudaEventRecord(H.ev_fork, st);
  cudaStreamWaitEvent(H.s2, H.ev_fork, 0);
  launch_rec(st, (const bf16*)d_in[4]);
  launch_A(H.s2, (bf16*)d_out);
  launch_Bout(st, (bf16*)d_out);
  cudaEventRecord(H.ev_join, H.s2);
  cudaStreamWaitEvent(st, H.ev_join, 0);
}
```
